```python
import torch

def _softmax(x, axis=-1):
    return torch.softmax(x, dim=axis)
def _gelu(x):
    return torch.nn.functional.gelu(x, approximate="tanh")
def _silu(x):
    return torch.nn.functional.silu(x)
def _sigmoid(x):
    return torch.sigmoid(x)
def _layernorm(x, axis=-1, eps=1e-5):
    m = x.mean(dim=axis, keepdim=True)
    v = x.var(dim=axis, keepdim=True, unbiased=False)
    return (x - m) / torch.sqrt(v + eps)
def _scatter_add(tgt, idx, src, axis=0):
    return tgt.clone().index_add_(axis, idx, src)
def _segment_sum(src, seg, n):
    out = torch.zeros((n,) + src.shape[1:], dtype=src.dtype)
    return out.index_add_(0, seg, src)
def _pad(x, pw):
    flat = tuple(v for pair in reversed(pw) for v in pair)
    return torch.nn.functional.pad(x, flat)

kernel_name = 'sequential_preLN__sliding_block_cached__glu_gated_geglu__decode'

def setup_inputs():

    _w = (lambda a: (lambda t: t.to(torch.bfloat16) if t.is_floating_point() else t)(torch.as_tensor(a)))
    def _A_setup():
        B, Sq, D = 2, 1, 512
        Hq, Hkv, Sk, Dh = 32, 8, 8192, 128
        assert Hq % Hkv == 0, (Hq, Hkv)
        return {
            "x": _w((lambda *s: torch.randn(*s, dtype=torch.bfloat16) * 0.05)(B, Sq, D)),
            "k_cache": _w((lambda *s: torch.randn(*s, dtype=torch.bfloat16) * 1.6)(B, Hkv, Sk, Dh)),
            "v_cache": _w((lambda *s: torch.randn(*s, dtype=torch.bfloat16) * 0.8)(B, Hkv, Sk, Dh)),
            "wq": _w((lambda *s: torch.randn(*s, dtype=torch.bfloat16) * 1.6)(D, Hq * Dh) * (D ** -0.5)),
            "wo": _w((lambda *s: torch.randn(*s, dtype=torch.bfloat16) * 0.8)(Hq * Dh, D) * ((Hq * Dh) ** -0.5)),
        }
    _A_in = _A_setup()

    def _B_setup():
        B, S, Dm, Df = 2, 1, 512, 1792
        return {
            "x": _w((lambda *s: torch.randn(*s, dtype=torch.bfloat16) * 0.05)(B, S, Dm)),
            "w_gate": _w((lambda *s: torch.randn(*s, dtype=torch.bfloat16) * 0.8)(Dm, Df) * (Dm ** -0.5)),
            "w_up": _w((lambda *s: torch.randn(*s, dtype=torch.bfloat16) * 0.8)(Dm, Df) * (Dm ** -0.5)),
            "w_down": _w((lambda *s: torch.randn(*s, dtype=torch.bfloat16) * 0.8)(Df, Dm) * (Df ** -0.5)),
        }
    _B_in = _B_setup()

    return {
        "A_x": _A_in["x"],
        "A_k_cache": _A_in["k_cache"],
        "A_v_cache": _A_in["v_cache"],
        "A_wq": _A_in["wq"],
        "A_wo": _A_in["wo"],
        "B_x": _B_in["x"],
        "B_w_gate": _B_in["w_gate"],
        "B_w_up": _B_in["w_up"],
        "B_w_down": _B_in["w_down"],
    }

def reference(A_x, A_k_cache, A_v_cache, A_wq, A_wo, B_x, B_w_gate, B_w_up, B_w_down):
    def _A_ref(x, k_cache, v_cache, wq, wo):
        B, Sq, D = x.shape
        Hq, Dh = 32, 128
        Hkv, Sk = k_cache.shape[1], k_cache.shape[2]
        W = min(4096, max(256, Sk // 4))
        rep = Hq // Hkv
        q = (lambda x, *d: x.permute(*d))((x @ wq).reshape(B, Sq, Hq, Dh), 0, 2, 1, 3)
        k = (lambda x, n, axis: torch.repeat_interleave(x, n, dim=axis))(k_cache[:, :, Sk - W:, :], rep, axis=1)
        v = (lambda x, n, axis: torch.repeat_interleave(x, n, dim=axis))(v_cache[:, :, Sk - W:, :], rep, axis=1)
        scores = torch.einsum("bhqd,bhkd->bhqk", q, k) * (Dh ** -0.5)
        p = _softmax(scores, axis=-1)
        o = torch.einsum("bhqk,bhkd->bhqd", p, v)
        return (lambda x, *d: x.permute(*d))(o, 0, 2, 1, 3).reshape(B, Sq, Hq * Dh) @ wo

    def _B_ref(x, w_gate, w_up, w_down):
        g = torch.einsum("bsd,df->bsf", x, w_gate)
        u = torch.einsum("bsd,df->bsf", x, w_up)
        h = _gelu(g) * u
        return torch.einsum("bsf,fd->bsd", h, w_down)

    x = A_x
    h = x + _A_ref(_layernorm(x, axis=-1), A_k_cache, A_v_cache, A_wq, A_wo)
    h2 = h + _B_ref(_layernorm(h, axis=-1), B_w_gate, B_w_up, B_w_down)
    return h2
```

```cpp
#include <cuda_runtime.h>
#include <cuda_bf16.h>
#include <cuda.h>
#include <stdint.h>

namespace {

typedef __nv_bfloat16 bf16;

constexpr int NCTA = 64;
constexpr int NCW = 16;
constexpr int NTHREADS = NCW * 32 + 96;
constexpr int NSLOT = 12;
constexpr int SLOT = 16384;
constexpr int NUNIT = 30;
#define WINDOW 10
#define PACE_NS 330
#define PACE0_NS 500
#define PACE_GU (PACE_NS * 7 / 8)
#define GU_GAP 300
#define TOUCH 0
#define WD_GAP 450

constexpr int OFF_XN = NSLOT * SLOT;
constexpr int OFF_Q = OFF_XN + 2112;
constexpr int OFF_QP = OFF_Q + 1088;
constexpr int OFF_S = OFF_QP + 2048;
constexpr int OFF_GIN = OFF_S;
constexpr int OFF_GST = OFF_GIN + 3584;
constexpr int OFF_SIN = OFF_GST + 128;
constexpr int OFF_P = OFF_S + 8192;
constexpr int OFF_RED = OFF_P + 4160;
constexpr int OFF_CIN = OFF_RED + 128;
constexpr int OFF_CML = OFF_CIN + 4096;
constexpr int OFF_H = OFF_CML + 64;
constexpr int OFF_OIN = OFF_H + 288;
constexpr int OFF_BAR = OFF_OIN + 1088;
constexpr int BAR_Q = 30, BAR_C = 31, BAR_Y = 32, BAR_G = 33, BAR_O = 34, BAR_S = 35, BAR_A = 36, BAR_X = 37, BAR_EMPTY = 40;
constexpr int OFF_PROF = OFF_BAR + 64 * 8;
constexpr int SMEM_BYTES = OFF_PROF + 256;
static_assert(SMEM_BYTES <= 232448, "smem");
static_assert(OFF_SIN + 1792 <= OFF_P, "alias");
static_assert(OFF_CIN % 16 == 0 && OFF_OIN % 16 == 0 && OFF_S % 16 == 0 && OFF_BAR % 8 == 0 && OFF_P % 16 == 0 && OFF_QP % 16 == 0, "align");
constexpr uint32_t EMPTY = 0xFFFFFFFFu;

__device__ __align__(128) uint32_t g_y[NCTA * 128];
__device__ __align__(128) uint32_t g_hh[NCTA * 32];
__device__ unsigned int g_ready;

#define STAMP(i) do { } while (0)
#define LSTAMP(cond, i) do { if (cond) STAMP(i); } while (0)

__device__ __forceinline__ uint32_t smem_u32(const void* p) { return (uint32_t)__cvta_generic_to_shared(p); }
__device__ __forceinline__ void mbar_init(uint32_t bar, int cnt) { asm volatile("mbarrier.init.shared::cta.b64 [%0], %1;" ::"r"(bar), "r"(cnt) : "memory"); }
__device__ __forceinline__ void mbar_expect(uint32_t bar, uint32_t bytes) { asm volatile("mbarrier.arrive.expect_tx.shared::cta.b64 _, [%0], %1;" ::"r"(bar), "r"(bytes) : "memory"); }
__device__ __forceinline__ void mbar_arrive(uint32_t bar) { asm volatile("mbarrier.arrive.shared::cta.b64 _, [%0];" ::"r"(bar) : "memory"); }
__device__ __forceinline__ bool mbar_try(uint32_t bar) {
    uint32_t ok;
    asm volatile("{\n.reg .pred p;\nmbarrier.try_wait.parity.shared::cta.b64 p, [%1], 0;\nselp.u32 %0, 1, 0, p;\n}" : "=r"(ok) : "r"(bar) : "memory");
    return ok;
}
__device__ __forceinline__ void mbar_wait(uint32_t bar) {
    int it = 0;
    while (!mbar_try(bar)) { if (++it > (1 << 22)) __trap(); }
}
__device__ __forceinline__ void tma2d(uint32_t dst, const CUtensorMap* map, int c0, int c1, uint32_t bar, uint64_t pol) {
    asm volatile("cp.async.bulk.tensor.2d.shared::cluster.global.mbarrier::complete_tx::bytes.L2::cache_hint [%0], [%1, {%3, %4}], [%2], %5;"
                 ::"r"(dst), "l"(map), "r"(bar), "r"(c0), "r"(c1), "l"(pol) : "memory");
}
__device__ __forceinline__ void tma3d(uint32_t dst, const CUtensorMap* map, int c0, int c1, int c2, uint32_t bar, uint64_t pol) {
    asm volatile("cp.async.bulk.tensor.3d.shared::cluster.global.mbarrier::complete_tx::bytes.L2::cache_hint [%0], [%1, {%3, %4, %5}], [%2], %6;"
                 ::"r"(dst), "l"(map), "r"(bar), "r"(c0), "r"(c1), "r"(c2), "l"(pol) : "memory");
}
__device__ __forceinline__ void tmap_prefetch(const CUtensorMap* m) { asm volatile("prefetch.tensormap [%0];" ::"l"(m) : "memory"); }
__device__ __forceinline__ uint32_t mapa(uint32_t a, uint32_t rank) { uint32_t d; asm("mapa.shared::cluster.u32 %0, %1, %2;" : "=r"(d) : "r"(a), "r"(rank)); return d; }
__device__ __forceinline__ void st_async1(uint32_t a, uint32_t v, uint32_t bar) {
    asm volatile("st.async.weak.shared::cluster.mbarrier::complete_tx::bytes.b32 [%0], %1, [%2];" ::"r"(a), "r"(v), "r"(bar) : "memory");
}
__device__ __forceinline__ void st_async2(uint32_t a, float v0, float v1, uint32_t bar) {
    asm volatile("st.async.weak.shared::cluster.mbarrier::complete_tx::bytes.v2.f32 [%0], {%1, %2}, [%3];" ::"r"(a), "f"(v0), "f"(v1), "r"(bar) : "memory");
}
__device__ __forceinline__ void st_async4(uint32_t a, float v0, float v1, float v2, float v3, uint32_t bar) {
    asm volatile("st.async.weak.shared::cluster.mbarrier::complete_tx::bytes.v4.f32 [%0], {%1, %2, %3, %4}, [%5];" ::"r"(a), "f"(v0), "f"(v1), "f"(v2), "f"(v3), "r"(bar) : "memory");
}
__device__ __forceinline__ void ldsm4(uint32_t (&r)[4], uint32_t a) {
    asm volatile("ldmatrix.sync.aligned.m8n8.x4.shared.b16 {%0,%1,%2,%3}, [%4];" : "=r"(r[0]), "=r"(r[1]), "=r"(r[2]), "=r"(r[3]) : "r"(a) : "memory");
}
__device__ __forceinline__ void ldsm4t(uint32_t (&r)[4], uint32_t a) {
    asm volatile("ldmatrix.sync.aligned.m8n8.x4.trans.shared.b16 {%0,%1,%2,%3}, [%4];" : "=r"(r[0]), "=r"(r[1]), "=r"(r[2]), "=r"(r[3]) : "r"(a) : "memory");
}
__device__ __forceinline__ void mma(float (&c)[4], const uint32_t (&a)[4], uint32_t b0, uint32_t b1) {
    asm volatile("mma.sync.aligned.m16n8k16.row.col.f32.bf16.bf16.f32 {%0,%1,%2,%3}, {%4,%5,%6,%7}, {%8,%9}, {%0,%1,%2,%3};"
                 : "+f"(c[0]), "+f"(c[1]), "+f"(c[2]), "+f"(c[3]) : "r"(a[0]), "r"(a[1]), "r"(a[2]), "r"(a[3]), "r"(b0), "r"(b1));
}
__device__ __forceinline__ uint32_t lds32(uint32_t a) { uint32_t v; asm volatile("ld.shared.b32 %0, [%1];" : "=r"(v) : "r"(a) : "memory"); return v; }
__device__ __forceinline__ float ldsf(uint32_t a) { float v; asm volatile("ld.shared.f32 %0, [%1];" : "=f"(v) : "r"(a) : "memory"); return v; }
__device__ __forceinline__ float2 ldsf2(uint32_t a) { float2 v; asm volatile("ld.shared.v2.f32 {%0,%1}, [%2];" : "=f"(v.x), "=f"(v.y) : "r"(a) : "memory"); return v; }
__device__ __forceinline__ float4 ldsf4(uint32_t a) { float4 v; asm volatile("ld.shared.v4.f32 {%0,%1,%2,%3}, [%4];" : "=f"(v.x), "=f"(v.y), "=f"(v.z), "=f"(v.w) : "r"(a) : "memory"); return v; }
__device__ __forceinline__ void stsf(uint32_t a, float v) { asm volatile("st.shared.f32 [%0], %1;" ::"r"(a), "f"(v) : "memory"); }
__device__ __forceinline__ void stsf2(uint32_t a, float v0, float v1) { asm volatile("st.shared.v2.f32 [%0], {%1,%2};" ::"r"(a), "f"(v0), "f"(v1) : "memory"); }
__device__ __forceinline__ void sts64(uint32_t a, uint32_t v0, uint32_t v1) { asm volatile("st.shared.v2.b32 [%0], {%1,%2};" ::"r"(a), "r"(v0), "r"(v1) : "memory"); }
__device__ __forceinline__ void sts128(uint32_t a, uint4 v) { asm volatile("st.shared.v4.b32 [%0], {%1,%2,%3,%4};" ::"r"(a), "r"(v.x), "r"(v.y), "r"(v.z), "r"(v.w) : "memory"); }
__device__ __forceinline__ void sts16(uint32_t a, uint16_t v) { asm volatile("st.shared.b16 [%0], %1;" ::"r"(a), "h"(v) : "memory"); }
__device__ __forceinline__ uint32_t ldg_acq(const uint32_t* p) { uint32_t v; asm volatile("ld.acquire.gpu.global.b32 %0, [%1];" : "=r"(v) : "l"(p) : "memory"); return v; }
__device__ __forceinline__ uint2 ldg_rlx2(const uint32_t* p) { uint2 v; asm volatile("ld.relaxed.gpu.global.v2.b32 {%0,%1}, [%2];" : "=r"(v.x), "=r"(v.y) : "l"(p) : "memory"); return v; }
__device__ __forceinline__ uint4 ldg_rlx4(const uint32_t* p) { uint4 v; asm volatile("ld.relaxed.gpu.global.v4.b32 {%0,%1,%2,%3}, [%4];" : "=r"(v.x), "=r"(v.y), "=r"(v.z), "=r"(v.w) : "l"(p) : "memory"); return v; }
__device__ __forceinline__ void stg_rlx(uint32_t* p, uint32_t v) { asm volatile("st.relaxed.gpu.global.b32 [%0], %1;" ::"l"(p), "r"(v) : "memory"); }
__device__ __forceinline__ void stg_rlx2(uint32_t* p, uint32_t a, uint32_t b) { asm volatile("st.relaxed.gpu.global.v2.b32 [%0], {%1,%2};" ::"l"(p), "r"(a), "r"(b) : "memory"); }
__device__ __forceinline__ void bar_compute() { asm volatile("bar.sync 1, 512;" ::: "memory"); }

__device__ __forceinline__ float bfr(float v) { uint32_t d; asm("cvt.rn.bf16x2.f32 %0, %1, %2;" : "=r"(d) : "f"(v), "f"(0.f)); return __uint_as_float(d); }
__device__ __forceinline__ uint32_t pack2(float lo, float hi) { uint32_t d; asm("cvt.rn.bf16x2.f32 %0, %1, %2;" : "=r"(d) : "f"(hi), "f"(lo)); return d; }
__device__ __forceinline__ float bf_lo(uint32_t v) { return __uint_as_float(v << 16); }
__device__ __forceinline__ float bf_hi(uint32_t v) { return __uint_as_float(v & 0xffff0000u); }
__device__ __forceinline__ float fsel(bool p, float a, float b) { float d; asm("{\n.reg .pred q;\nsetp.ne.u32 q, %3, 0;\nselp.f32 %0, %1, %2, q;\n}" : "=f"(d) : "f"(a), "f"(b), "r"((uint32_t)p)); return d; }
__device__ __forceinline__ float rcp(float x) { float y; asm("rcp.approx.ftz.f32 %0, %1;" : "=f"(y) : "f"(x)); return y; }
__device__ __forceinline__ float ex2(float x) { float y; asm("ex2.approx.ftz.f32 %0, %1;" : "=f"(y) : "f"(x)); return y; }
__device__ __forceinline__ uint32_t pin(uint32_t v) { asm volatile("" : "+r"(v)); return v; }
template <class T> __device__ __forceinline__ T* pinp(T* v) { asm volatile("" : "+l"(v)); return v; }
__device__ __forceinline__ bool elect_one() { uint32_t p; asm volatile("{\n.reg .pred q;\nelect.sync _|q, 0xffffffff;\nselp.u32 %0, 1, 0, q;\n}" : "=r"(p)); return p; }
__device__ __forceinline__ unsigned int now_ns() { unsigned int t; asm volatile("mov.u32 %0, %%globaltimer_lo;" : "=r"(t)); return t; }
__device__ __forceinline__ float ln_rstd(float m2) {
    float sq;
    asm("sqrt.approx.ftz.f32 %0, %1;" : "=f"(sq) : "f"(bfr(bfr(m2 * (1.f / 512.f)) + 1e-5f)));
    return rcp(bfr(sq));
}
#define SUM8(v, f) (((v[0] f + v[1] f) + (v[2] f + v[3] f)) + ((v[4] f + v[5] f) + (v[6] f + v[7] f)))

struct Ptrs { const bf16* x; bf16* out; uint32_t *gy, *ghh, *ready; const unsigned char *wq, *k, *v, *wo, *wg, *wu, *wd; };

__global__ void __cluster_dims__(8, 1, 1) __launch_bounds__(NTHREADS, 1)
fused_decode_kernel(const Ptrs ptrs, const __grid_constant__ CUtensorMap mq, const __grid_constant__ CUtensorMap mk,
                    const __grid_constant__ CUtensorMap mv, const __grid_constant__ CUtensorMap mo, const __grid_constant__ CUtensorMap mg,
                    const __grid_constant__ CUtensorMap mu, const __grid_constant__ CUtensorMap md) {
    extern __shared__ __align__(1024) unsigned char smem_raw[];
    const uint32_t sb = smem_u32(smem_raw);
    const int tid = threadIdx.x, warp = __shfl_sync(~0u, tid >> 5, 0), lane = tid & 31;
    const int c = blockIdx.x >> 3;
    const int r = blockIdx.x & 7;
    const uint32_t bars = sb + OFF_BAR;
#define WAIT(b) mbar_wait(bars + 8 * (b))
#define ARRIVE(b) do { __syncwarp(); if (lane == 0) mbar_arrive(bars + 8 * (b)); } while (0)

    uint64_t pol;
    asm volatile("createpolicy.fractional.L2::evict_first.b64 %0, 1.0;" : "=l"(pol));
    const unsigned int tg0 = now_ns();
    if (tid == NCW * 32) {
        tmap_prefetch(&mq);
        asm volatile("cp.async.bulk.prefetch.L2.global.L2::cache_hint [%0], %1, %2;" ::"l"(ptrs.wq + blockIdx.x * 16384), "r"(16384), "l"(pol) : "memory");
#pragma unroll
        for (int u = 0; u < 4; u++) {
            mbar_init(bars + 8 * u, 1);
            mbar_expect(bars + 8 * u, SLOT);
            tma2d(sb + u * SLOT, &mq, c * 512 + r * 64, u * 128, bars + 8 * u, pol);
        }
        STAMP(28);
    }
    uint4 v0 = make_uint4(0u, 0u, 0u, 0u), v1 = v0;
    asm volatile("{\n.reg .pred p;\nsetp.ne.u32 p, %9, 0;\n@p ld.global.nc.v4.u32 {%0,%1,%2,%3}, [%8];\n@p ld.global.nc.v4.u32 {%4,%5,%6,%7}, [%8+512];\n}"
                 : "+r"(v0.x), "+r"(v0.y), "+r"(v0.z), "+r"(v0.w), "+r"(v1.x), "+r"(v1.y), "+r"(v1.z), "+r"(v1.w)
                 : "l"(ptrs.x + (warp & 1) * 512 + lane * 8), "r"((uint32_t)(warp < 2)));
    if (warp == NCW + 1 || warp == NCW + 2) {
        stg_rlx2(ptrs.gy + blockIdx.x * 128 + (tid - (NCW + 1) * 32) * 2, EMPTY, EMPTY);
        if (lane < 16) stg_rlx(ptrs.ghh + blockIdx.x * 32 + (warp - NCW - 1) * 16 + lane, EMPTY);
        if (tid == (NCW + 1) * 32) tmap_prefetch(&mk);
    }
    if (warp >= 2 && warp < 14 && elect_one()) {
        const int j = warp - 2;
        const uint32_t b = bars + 8 * (4 + j);
        mbar_init(b, 1);
        mbar_init(b + 8 * 12, 1);
        mbar_init(b + 8 * 24, j == BAR_X - 28 ? 2 : 1);
        mbar_init(b + 8 * 36, j < 4 ? NCW : 4);
        if (j < 6) mbar_init(b + 8 * 48, NCW);
        if (j >= 2 && j < 9 && j != 4) mbar_expect(b + 8 * 24, j == 2 ? 1024u : j == 3 ? 4160u : j == 5 ? 3712u : j == 6 ? 1088u : j == 7 ? 1792u : 2048u);
    }
    asm volatile("fence.mbarrier_init.release.cluster;" ::: "memory");
    __syncthreads();
    asm volatile("barrier.cluster.arrive.relaxed.aligned;" ::: "memory");

    if (warp < 2) {
        const uint32_t xw[8] = {v0.x, v0.y, v0.z, v0.w, v1.x, v1.y, v1.z, v1.w};
        float f[16], s = 0.f;
#pragma unroll
        for (int i = 0; i < 8; i++) { f[2 * i] = bf_lo(xw[i]); f[2 * i + 1] = bf_hi(xw[i]); s += f[2 * i] + f[2 * i + 1]; }
#pragma unroll
        for (int o = 16; o; o >>= 1) s += __shfl_xor_sync(~0u, s, o);
        const float mean = s * (1.f / 512.f);
        float q = 0.f;
#pragma unroll
        for (int i = 0; i < 16; i++) { const float d = f[i] - mean; q += d * d; }
#pragma unroll
        for (int o = 16; o; o >>= 1) q += __shfl_xor_sync(~0u, q, o);
        const float mb = bfr(mean), rd = ln_rstd(q);
        uint32_t o8[8];
#pragma unroll
        for (int i = 0; i < 8; i++) o8[i] = pack2(bfr(f[2 * i] - mb) * rd, bfr(f[2 * i + 1] - mb) * rd);
        sts128(sb + OFF_XN + warp * 1040 + lane * 16, make_uint4(o8[0], o8[1], o8[2], o8[3]));
        sts128(sb + OFF_XN + warp * 1040 + 512 + lane * 16, make_uint4(o8[4], o8[5], o8[6], o8[7]));
        ARRIVE(BAR_X);
    }
    const int g = lane >> 2, t = lane & 3;

    if (warp == NCW) {
        if (lane == 0) {
            STAMP(29);
            const int kvrow = ((r >> 2) * 8 + c) * 8192 + 6144 + (r & 3) * 64;
            unsigned int due = tg0 + PACE0_NS + (PACE_NS * blockIdx.x) / 64;
#pragma unroll 1
            for (int u = 4; u < NUNIT; u++) {
                const int slot = u >= 24 ? u - 24 : u >= 12 ? u - 12 : u;
                const uint32_t dst = sb + slot * SLOT, fb = bars + 8 * u;
                if (u >= NSLOT) WAIT(BAR_EMPTY + u - NSLOT);
                if (u >= WINDOW) WAIT(u - WINDOW);
                if (u == 28) {
                    WAIT(BAR_Y);
                    due = now_ns() + WD_GAP;
                }
                while ((int)(now_ns() - due) < 0) { }
                due += u >= 28 ? 0 : u >= 24 ? PACE_GU : u == 23 ? PACE_NS + GU_GAP : PACE_NS;
                if (u < 12) { mbar_expect(fb, SLOT); tma3d(dst, &mk, 0, kvrow + (u - 4) * 256, 0, fb, pol); }
                else if (u < 20) { mbar_expect(fb, SLOT); tma3d(dst, &mv, 0, kvrow + (u - 12) * 256, 0, fb, pol); }
                else if (u < 24) { mbar_expect(fb, SLOT); tma2d(dst, &mo, r * 64, c * 512 + (u - 20) * 128, fb, pol); }
                else if (u < 28) {
                    mbar_expect(fb, 14336);
                    tma3d(dst, &mg, 0, r * 64 + (u - 24) * 16, c * 7, fb, pol);
                    tma3d(dst + 8192, &mu, 0, r * 64 + (u - 24) * 16, c * 7, fb, pol);
                } else { mbar_expect(fb, 14336); tma2d(dst, &md, c * 64, r * 224 + (u - 28) * 112, fb, pol); }
            }
            STAMP(20);
        }
        return;
    }
    if (warp > NCW) {
        const int b = warp - NCW - 1, e = b * 32 + lane;
        if (b == 0) {
            if (lane == 1) tmap_prefetch(&mv);
            if (lane == 2) tmap_prefetch(&mo);
            if (lane == 3) tmap_prefetch(&mg);
            if (lane == 4) tmap_prefetch(&mu);
            if (lane == 5) tmap_prefetch(&md);
        }
        const float x0 = __bfloat162float(ptrs.x[r * 64 + e]), x1 = __bfloat162float(ptrs.x[512 + r * 64 + e]);
        asm volatile("fence.acq_rel.gpu;" ::: "memory");
        __syncwarp();
        if (lane == 0) {
            asm volatile("red.relaxed.gpu.global.add.u32 [%0], 1;" ::"l"(ptrs.ready) : "memory");
            int it = 0;
            while (ldg_acq(ptrs.ready) < 2u * NCTA) { __nanosleep(500); if (++it > (1 << 22)) __trap(); }
        }
        __syncwarp();
        asm volatile("barrier.cluster.wait.aligned;" ::: "memory");
        LSTAMP(tid == 544, 19);
        {
            uint32_t* ypub = pinp(ptrs.gy + blockIdx.x * 128 + e * 2);
            const uint32_t* src = pinp(ptrs.gy + r * 128 + e * 2);
            const uint32_t yin = pin(sb + OFF_QP + e * 8), hdst = pin(sb + OFF_H + e * 2), boff = pin(sb + OFF_H + (g & 1) * 144 + t * 4);
            const int srk = (g >> 1) * 2 + (t >> 1);
            const uint32_t sdst = pin(mapa(sb + OFF_GST + r * 16 + (g & 1) * 8 + ((t & 1) ? 0 : 4), srk)), sbar = pin(mapa(bars + 8 * BAR_G, srk));
            asm volatile("bar.sync 3, 576;" ::: "memory");
            {
                const float2 p0 = ldsf2(yin), p1 = ldsf2(yin + 512), p2 = ldsf2(yin + 1024), p3 = ldsf2(yin + 1536);
                stg_rlx2(ypub, __float_as_uint((p0.x + p1.x) + (p2.x + p3.x)), __float_as_uint((p0.y + p1.y) + (p2.y + p3.y)));
            }
            LSTAMP(tid == 544, 8);
            if (tid == (NCW + 1) * 32) mbar_arrive(bars + 8 * BAR_Y);
            float y0, y1;
            for (int it = 0;; it++) {
                float2 v[8];
#pragma unroll
                for (int s = 0; s < 8; s++) { const uint2 u = ldg_rlx2(src + s * 1024); v[s] = make_float2(__uint_as_float(u.x), __uint_as_float(u.y)); }
                y0 = SUM8(v, .x);
                y1 = SUM8(v, .y);
                if (!__any_sync(~0u, (y0 + y1) != (y0 + y1))) break;
                if (it > 64) {
                    uint32_t mx = 0u;
#pragma unroll
                    for (int s = 0; s < 8; s++) mx = max(mx, max(__float_as_uint(v[s].x), __float_as_uint(v[s].y)));
                    if (!__any_sync(~0u, mx == EMPTY)) break;
                    if (it > (1 << 22)) __trap();
                }
            }
            LSTAMP(tid == 544, 9);
            const uint32_t hp = pack2(x0 + bfr(y0), x1 + bfr(y1));
            sts16(hdst, (uint16_t)hp);
            sts16(hdst + 144, (uint16_t)(hp >> 16));
            asm volatile("bar.sync 2, 512;" ::: "memory");
            uint32_t hf[8];
#pragma unroll
            for (int i = 0; i < 8; i++) hf[i] = lds32(boff + i * 16);
            float s0[4] = {0.f, 0.f, 0.f, 0.f}, s1[4] = {0.f, 0.f, 0.f, 0.f};
#pragma unroll
            for (int i = 0; i < 4; i++) {
                const uint32_t a[4] = {hf[2 * i], 0u, hf[2 * i + 1], 0u};
                const uint32_t b0 = (g & 2) ? 0x3F803F80u : hf[2 * i], b1 = (g & 2) ? 0x3F803F80u : hf[2 * i + 1];
                if (i & 1) mma(s1, a, b0, b1); else mma(s0, a, b0, b1);
            }
            const float sv = fsel((g & 1) && !(t & 1), s0[1] + s1[1], s0[0] + s1[0]);
            if ((g & 1) == b) st_async1(sdst, __float_as_uint(sv), sbar);
            if (r == c) st_async2(mapa(sb + OFF_OIN + 1024 + (e & 7) * 8, e >> 3), bf_lo(hp), bf_hi(hp), mapa(bars + 8 * BAR_O, e >> 3));
        }
        {
            const int lc = lane < 28 ? lane : 27;
            uint32_t* hpub = pinp(ptrs.ghh + blockIdx.x * 32 + b * 16 + (lane >> 1));
            const uint32_t gst = pin(sb + OFF_GST + b * 8), gin = pin(sb + OFF_GIN + lc * 16 + b * 8);
            float2 st[8], v[8];
            WAIT(BAR_S);
#pragma unroll
            for (int s = 0; s < 8; s++) v[s] = ldsf2(sb + OFF_SIN + s * 224 + lc * 8);
            const float gs = SUM8(v, .x), us = SUM8(v, .y);
            WAIT(BAR_G);
            LSTAMP(tid == 544, 12);
#pragma unroll
            for (int s = 0; s < 8; s++) st[s] = ldsf2(gst + s * 16);
#pragma unroll
            for (int s = 0; s < 8; s++) v[s] = ldsf2(gin + s * 448);
            const float mu = SUM8(st, .x) * (1.f / 512.f);
            const float rs = ln_rstd(fmaxf(fmaf(-512.f * mu, mu, SUM8(st, .y)), 0.f)), mb = bfr(mu);
            const float ga = bfr(fmaf(-mb, gs, SUM8(v, .x)) * rs), ua = bfr(fmaf(-mb, us, SUM8(v, .y)) * rs);
            const float K2 = -2.f * 0.7978845608028654f * 1.4426950408889634f;
            const float ea = ex2(ga * fmaf(K2 * 0.044715f * ga, ga, K2));
            const float ha = bfr(ga * rcp(1.f + ea)) * ua;
            const uint32_t wd = pack2(ha, __shfl_down_sync(~0u, ha, 1));
            if (!(lane & 1)) stg_rlx(hpub, wd);
            LSTAMP(tid == 544, 13);
        }
        if (b == 0) {
            const int l = lane & 15;
            bf16* dsto = pinp(ptrs.out + (l & 1) * 512 + c * 64 + r * 8 + (l >> 1));
            const uint32_t oin = pin(sb + OFF_OIN + l * 4);
            WAIT(BAR_O);
            LSTAMP(lane == 0, 16);
            float p[8], q[8];
#pragma unroll
            for (int s = 0; s < 8; s++) { p[s] = ldsf(oin + s * 64); q[s] = ldsf(oin + 512 + s * 64); }
            const float hf = ldsf(oin + 1024);
            if (lane < 16) *reinterpret_cast<uint16_t*>(dsto) = (uint16_t)pack2(hf + bfr(SUM8(p, ) + SUM8(q, )), 0.f);
            if (blockIdx.x == 0 && lane == 16) stg_rlx(ptrs.ready, 0u);
            LSTAMP(lane == 0, 17);
        }
        return;
    }

    const int w = warp;
    const int lrow = lane & 7, lm1 = (lane >> 3) & 1, lm2 = lane >> 4;
    const float L2E = 1.4426950408889634f;
    const uint32_t gv_a = sb + (uint32_t)(((w >> 2) * 32 + lrow + 8 * lm2) * 128 + (((2 * (w & 3) + lm1) ^ lrow) << 4));
    const uint32_t gv_b = sb + OFF_XN + (g & 1) * 1040 + ((w >> 2) * 32 + 2 * t) * 2;
    const uint32_t gv_d = pin(sb + OFF_QP + ((w >> 2) * 64 + (w & 3) * 16 + g + 8 * (t & 1)) * 8);
#define GEMV512(UNIT0, SLOT0, RELEASE)                                                                                                    \
    {                                                                                                                                     \
        float acc0[4] = {0.f, 0.f, 0.f, 0.f}, acc1[4] = {0.f, 0.f, 0.f, 0.f};                                                             \
        _Pragma("unroll 1") for (int u = 0; u < 4; u++) {                                                                                 \
            const uint32_t b0 = lds32(gv_b + u * 256), b1 = lds32(gv_b + u * 256 + 16), b2 = lds32(gv_b + u * 256 + 32), b3 = lds32(gv_b + u * 256 + 48); \
            WAIT(UNIT0 + u);                                                                                                              \
            uint32_t a0[4], a1[4];                                                                                                        \
            ldsm4t(a0, gv_a + (SLOT0 + u) * SLOT);                                                                                        \
            ldsm4t(a1, gv_a + (SLOT0 + u) * SLOT + 2048);                                                                                 \
            mma(acc0, a0, b0, b1);                                                                                                        \
            mma(acc1, a1, b2, b3);                                                                                                        \
            if (RELEASE) ARRIVE(BAR_EMPTY + u);                                                                                           \
        }                                                                                                                                 \
        if (t < 2) stsf2(gv_d, fsel(t, acc0[2] + acc1[2], acc0[0] + acc1[0]), fsel(t, acc0[3] + acc1[3], acc0[1] + acc1[1]));             \
    }
    {
        WAIT(BAR_X);
        LSTAMP(tid == 0, 0);
        GEMV512(0, 0, true);
        asm volatile("barrier.cluster.wait.aligned;" ::: "memory");
        bar_compute();
        if (tid < 32) {
            float s[4] = {0.f, 0.f, 0.f, 0.f};
#pragma unroll
            for (int k = 0; k < 4; k++) { const float4 v = ldsf4(sb + OFF_QP + k * 512 + lane * 16); s[0] += v.x; s[1] += v.y; s[2] += v.z; s[3] += v.w; }
            const uint32_t w0 = pack2(s[0], s[2]), w1 = pack2(s[1], s[3]);
            const uint32_t dst = mapa(sb + OFF_Q + (r >> 1) * 272 + ((r & 1) * 64 + lane * 2) * 2, 0), dbar = mapa(bars + 8 * BAR_Q, 0);
#pragma unroll
            for (int j = 0; j < 8; j++) st_async1(dst + (j << 24), j < 4 ? w0 : w1, dbar + (j << 24));
        }
        LSTAMP(tid == 0, 1);
    }
    {
        WAIT(BAR_Q);
        LSTAMP(tid == 0, 2);
        uint32_t qf[16];
#pragma unroll
        for (int ks = 0; ks < 8; ks++) {
            const uint32_t a = sb + OFF_Q + (g & 3) * 272 + (ks * 16 + 2 * t) * 2;
            qf[2 * ks] = lds32(a); qf[2 * ks + 1] = lds32(a + 16);
        }
        const int mt = w & 3;
#pragma unroll 1
        for (int j = w >> 2; j < 8; j += 4) {
            WAIT(4 + j);
            float acc0[4] = {0.f, 0.f, 0.f, 0.f}, acc1[4] = {0.f, 0.f, 0.f, 0.f};
            const uint32_t base = sb + (4 + j) * SLOT + (uint32_t)((mt * 16 + lrow + 8 * lm1) * 128);
#pragma unroll
            for (int ks = 0; ks < 4; ks++) {
                uint32_t a0[4], a1[4];
                const uint32_t sw = (uint32_t)(((2 * ks + lm2) ^ lrow) << 4);
                ldsm4(a0, base + sw);
                ldsm4(a1, base + 8192 + sw);
                mma(acc0, a0, qf[2 * ks], qf[2 * ks + 1]);
                mma(acc1, a1, qf[8 + 2 * ks], qf[8 + 2 * ks + 1]);
            }
            ARRIVE(BAR_EMPTY + 4 + j);
            const float sc = 0.08838834764831845f;
            const bool hi = t >> 1;
            const uint32_t p = sb + OFF_S + (2 * (t & 1) * 512 + j * 64 + mt * 16 + g + 8 * (t >> 1)) * 4;
            stsf(p, bfr(bfr(fsel(hi, acc0[2] + acc1[2], acc0[0] + acc1[0])) * sc));
            stsf(p + 2048, bfr(bfr(fsel(hi, acc0[3] + acc1[3], acc0[1] + acc1[1])) * sc));
        }
        bar_compute();
    }
    {
        const int h = w >> 2;
        const float4 s = ldsf4(sb + OFF_S + tid * 16);
        LSTAMP(tid == 0, 3);
        float m = fmaxf(fmaxf(s.x, s.y), fmaxf(s.z, s.w));
#pragma unroll
        for (int o = 16; o; o >>= 1) m = fmaxf(m, __shfl_xor_sync(~0u, m, o));
        if (lane == 0) stsf(sb + OFF_RED + w * 4, m);
        bar_compute();
        const float4 mm = ldsf4(sb + OFF_RED + h * 16);
        m = fmaxf(fmaxf(mm.x, mm.y), fmaxf(mm.z, mm.w));
        const float p0 = ex2((s.x - m) * L2E), p1 = ex2((s.y - m) * L2E), p2 = ex2((s.z - m) * L2E), p3 = ex2((s.w - m) * L2E);
        sts64(sb + OFF_P + h * 1040 + (tid & 127) * 8, pack2(p0, p1), pack2(p2, p3));
        float l = (p0 + p1) + (p2 + p3);
#pragma unroll
        for (int o = 16; o; o >>= 1) l += __shfl_xor_sync(~0u, l, o);
        if (lane == 0) stsf(sb + OFF_RED + 64 + w * 4, l);
        bar_compute();
        if (tid < 8) {
            const int hh = tid >> 1;
            const float4 a = ldsf4(sb + OFF_RED + hh * 16), b = ldsf4(sb + OFF_RED + 64 + hh * 16);
            st_async2(mapa(sb + OFF_CML + r * 8, tid), fmaxf(fmaxf(a.x, a.y), fmaxf(a.z, a.w)), (b.x + b.y) + (b.z + b.w), mapa(bars + 8 * BAR_C, tid));
        }
        LSTAMP(tid == 0, 4);
    }
    {
        const int mt = w & 7, kh = w >> 3;
        float acc0[4] = {0.f, 0.f, 0.f, 0.f}, acc1[4] = {0.f, 0.f, 0.f, 0.f};
        const uint32_t aoff = sb + (uint32_t)((mt >> 2) * 8192 + (kh * 32 + lrow + 8 * lm2) * 128 + (((2 * (mt & 3) + lm1) ^ lrow) << 4));
        const uint32_t boff = sb + OFF_P + (g & 3) * 1040 + (kh * 32 + 2 * t) * 2;
        const int hi = t >> 1, d = mt * 16 + g + 8 * hi, rk = 4 * (t & 1) + (d >> 6);
        const uint32_t dst = pin(mapa(sb + OFF_CIN + ((r * 2 + kh) * 64 + (d & 63)) * 4, rk)), dbar = pin(mapa(bars + 8 * BAR_C, rk));
#pragma unroll 1
        for (int j = 0; j < 8; j++) {
            const uint32_t b0 = lds32(boff + j * 128), b1 = lds32(boff + j * 128 + 16), b2 = lds32(boff + j * 128 + 32), b3 = lds32(boff + j * 128 + 48);
            WAIT(12 + j);
            uint32_t a0[4], a1[4];
            ldsm4t(a0, aoff + j * SLOT);
            ldsm4t(a1, aoff + j * SLOT + 2048);
            mma(acc0, a0, b0, b1);
            mma(acc1, a1, b2, b3);
            if (j < 6) ARRIVE(BAR_EMPTY + 12 + j);
        }
        st_async1(dst, __float_as_uint(fsel(hi, acc0[2] + acc1[2], acc0[0] + acc1[0])), dbar);
        st_async1(dst + (2u << 24), __float_as_uint(fsel(hi, acc0[3] + acc1[3], acc0[1] + acc1[1])), dbar + (2u << 24));
        LSTAMP(tid == 0, 5);
    }
    if (tid < 128) {
        const int b = tid >> 6, d = tid & 63;
        const uint32_t dst = pin(mapa(sb + OFF_XN + b * 1040 + (r * 64 + (d & ~1)) * 2, (lane & 1) * 4)), dbar = pin(mapa(bars + 8 * BAR_A, (lane & 1) * 4));
        const uint32_t p = pin(sb + OFF_CIN + (b * 512 + d) * 4);
        WAIT(BAR_C);
        const float4 ml0 = ldsf4(sb + OFF_CML + b * 32), ml1 = ldsf4(sb + OFF_CML + b * 32 + 16);
        const float o0 = ldsf(p) + ldsf(p + 256), o1 = ldsf(p + 512) + ldsf(p + 768), o2 = ldsf(p + 1024) + ldsf(p + 1280), o3 = ldsf(p + 1536) + ldsf(p + 1792);
        const float M = fmaxf(fmaxf(ml0.x, ml0.z), fmaxf(ml1.x, ml1.z));
        const float w0 = ex2((ml0.x - M) * L2E), w1 = ex2((ml0.z - M) * L2E), w2 = ex2((ml1.x - M) * L2E), w3 = ex2((ml1.z - M) * L2E);
        const float L = (w0 * ml0.y + w1 * ml0.w) + (w2 * ml1.y + w3 * ml1.w);
        const float ov = ((w0 * o0 + w1 * o1) + (w2 * o2 + w3 * o3)) * rcp(L);
        const float nb = __shfl_xor_sync(~0u, ov, 1);
        const uint32_t wd = (lane & 1) ? pack2(nb, ov) : pack2(ov, nb);
#pragma unroll
        for (int j = 0; j < 4; j++) st_async1(dst + (j << 24), wd, dbar + (j << 24));
        LSTAMP(tid == 0, 6);
    }
    {
        uint32_t a[8][4], bq[16];
#pragma unroll
        for (int u = 0; u < 3; u++) {
            WAIT(20 + u);
            ldsm4t(a[2 * u], gv_a + (8 + u) * SLOT);
            ldsm4t(a[2 * u + 1], gv_a + (8 + u) * SLOT + 2048);
        }
        WAIT(BAR_A);
        LSTAMP(tid == 0, 18);
#pragma unroll
        for (int i = 0; i < 16; i++) bq[i] = lds32(gv_b + (i >> 2) * 256 + (i & 3) * 16);
        float acc0[4] = {0.f, 0.f, 0.f, 0.f}, acc1[4] = {0.f, 0.f, 0.f, 0.f};
#pragma unroll
        for (int u = 0; u < 3; u++) { mma(acc0, a[2 * u], bq[4 * u], bq[4 * u + 1]); mma(acc1, a[2 * u + 1], bq[4 * u + 2], bq[4 * u + 3]); }
        WAIT(23);
        ldsm4t(a[6], gv_a + 11 * SLOT);
        ldsm4t(a[7], gv_a + 11 * SLOT + 2048);
        mma(acc0, a[6], bq[12], bq[13]);
        mma(acc1, a[7], bq[14], bq[15]);
        if (t < 2) stsf2(gv_d, fsel(t, acc0[2] + acc1[2], acc0[0] + acc1[0]), fsel(t, acc0[3] + acc1[3], acc0[1] + acc1[1]));
    }
    asm volatile("bar.arrive 3, 576;" ::: "memory");
    LSTAMP(tid == 0, 7);
    if (w >= 14) return;
    {
        uint32_t ag[4][4], au[4][4];
        const int row = lrow + 8 * lm2;
        const uint32_t aoff = sb + (uint32_t)((w >> 1) * 1024 + row * 64 + (((2 * (w & 1) + lm1) ^ ((row >> 1) & 3)) << 4));
        const int col = w * 16 + g + 8 * (t & 1), rk = col / 28, lc = col - rk * 28;
        const uint32_t dst = pin(mapa(sb + OFF_GIN + r * 448 + lc * 16, rk));
        const uint32_t dbar = pin(mapa(bars + 8 * BAR_G, rk));
        const bool hi = t & 1;
        {
            float g0[4] = {0.f, 0.f, 0.f, 0.f}, u0[4] = {0.f, 0.f, 0.f, 0.f};
#pragma unroll
            for (int j = 0; j < 4; j++) {
                WAIT(24 + j);
                ldsm4t(ag[j], aoff + j * SLOT);
                ldsm4t(au[j], aoff + j * SLOT + 8192);
                mma(g0, ag[j], 0x3F803F80u, 0x3F803F80u);
                mma(u0, au[j], 0x3F803F80u, 0x3F803F80u);
            }
            if (t < 2) st_async2(mapa(sb + OFF_SIN + r * 224 + lc * 8, rk), fsel(hi, g0[2], g0[0]), fsel(hi, u0[2], u0[0]), mapa(bars + 8 * BAR_S, rk));
        }
        const uint32_t boff = pin(sb + OFF_H + (g & 1) * 144 + t * 4);
        LSTAMP(tid == 0, 11);
        asm volatile("bar.sync 2, 512;" ::: "memory");
        uint32_t hf[8];
#pragma unroll
        for (int i = 0; i < 8; i++) hf[i] = lds32(boff + i * 16);
        float g0[4] = {0.f, 0.f, 0.f, 0.f}, u0[4] = {0.f, 0.f, 0.f, 0.f};
#pragma unroll
        for (int j = 0; j < 4; j++) { mma(g0, ag[j], hf[2 * j], hf[2 * j + 1]); mma(u0, au[j], hf[2 * j], hf[2 * j + 1]); }
        if (t < 2) st_async4(dst, fsel(hi, g0[2], g0[0]), fsel(hi, u0[2], u0[0]), fsel(hi, g0[3], g0[1]), fsel(hi, u0[3], u0[1]), dbar);
        LSTAMP(tid == 0, 10);
    }
    if (w >= 8) return;
    {
        const int mt = w & 3, kh = w >> 2;
        uint32_t ad[7][4];
        const uint32_t aoff = sb + (uint32_t)((4 + kh) * SLOT + (lrow + 8 * lm2) * 128 + (((2 * mt + lm1) ^ lrow) << 4));
        const uint32_t dst = pin(mapa(sb + OFF_OIN + ((r * 2 + kh) * 16 + g * 2) * 4, 2 * mt + (t & 1)));
        const uint32_t dbar = pin(mapa(bars + 8 * BAR_O, 2 * mt + (t & 1)));
        const uint32_t* src = pinp(ptrs.ghh + r * 256 + kh * 128 + lane * 4);
        const uint32_t stw = pin(sb + OFF_P + w * 512 + lane * 16);
        const uint32_t sta = pin(sb + OFF_P + w * 512 + (g & 1) * 64 + t * 4), stb = pin(sta + (t >= 2 ? 72 : 0));
        WAIT(28 + kh);
#pragma unroll
        for (int ks = 0; ks < 7; ks++) ldsm4t(ad[ks], aoff + ks * 2048);
        uint4 va;
        for (int it = 0;; it++) {
            va = ldg_rlx4(src);
            if (!__any_sync(~0u, max(max(va.x, va.y), max(va.z, va.w)) == EMPTY)) break;
            if (it > (1 << 22)) __trap();
        }
        sts128(stw, va);
        __syncwarp();
        uint32_t hw[14];
#pragma unroll
        for (int i = 0; i < 14; i++) {
            const int lo = (4 * i) / 14, hi2 = (4 * i + 3) / 14;
            hw[i] = lds32((lo == hi2 ? sta : stb) + 16 * i + 72 * lo);
        }
        LSTAMP(tid == 0, 14);
        float c0[4] = {0.f, 0.f, 0.f, 0.f}, c1[4] = {0.f, 0.f, 0.f, 0.f};
#pragma unroll
        for (int ks = 0; ks < 7; ks++) {
            if (ks & 1) mma(c1, ad[ks], hw[2 * ks], hw[2 * ks + 1]);
            else mma(c0, ad[ks], hw[2 * ks], hw[2 * ks + 1]);
        }
        if (t < 2) st_async2(dst, fsel(t, c0[2] + c1[2], c0[0] + c1[0]), fsel(t, c0[3] + c1[3], c0[1] + c1[1]), dbar);
        LSTAMP(tid == 0, 15);
    }
}

typedef CUresult (*EncodeFn)(CUtensorMap*, CUtensorMapDataType, cuuint32_t, void*, const cuuint64_t*, const cuuint64_t*, const cuuint32_t*,
                             const cuuint32_t*, CUtensorMapInterleave, CUtensorMapSwizzle, CUtensorMapL2promotion, CUtensorMapFloatOOBfill);

bool make_map(EncodeFn enc, CUtensorMap* m, const void* base, int rank, cuuint64_t d0, cuuint64_t d1, cuuint64_t d2, cuuint64_t s1, cuuint64_t s2,
              cuuint32_t b0, cuuint32_t b1, cuuint32_t b2, CUtensorMapSwizzle sw) {
    cuuint64_t gd[3] = {d0, d1, d2}, gs[2] = {s1, s2};
    cuuint32_t bd[3] = {b0, b1, b2}, es[3] = {1, 1, 1};
    return enc(m, CU_TENSOR_MAP_DATA_TYPE_BFLOAT16, rank, const_cast<void*>(base), gd, gs, bd, es, CU_TENSOR_MAP_INTERLEAVE_NONE, sw,
               CU_TENSOR_MAP_L2_PROMOTION_L2_256B, CU_TENSOR_MAP_FLOAT_OOB_FILL_NONE) == CUDA_SUCCESS;
}

}

extern "C" void kernel_launch(void* const* d_in, const int* in_sizes, int n_in, void* d_out, int out_size) {
    static EncodeFn enc = nullptr;
    static void *gy = nullptr, *ghh = nullptr, *gready = nullptr;
    if (!enc) {
        void* f = nullptr;
        cudaDriverEntryPointQueryResult qr;
        cudaGetDriverEntryPoint("cuTensorMapEncodeTiled", &f, cudaEnableDefault, &qr);
        enc = (EncodeFn)f;
        cudaGetSymbolAddress(&gy, g_y);
        cudaGetSymbolAddress(&ghh, g_hh);
        cudaGetSymbolAddress(&gready, g_ready);
        cudaFuncSetAttribute(fused_decode_kernel, cudaFuncAttributeMaxDynamicSharedMemorySize, SMEM_BYTES);
    }
    CUtensorMap mq, mk, mv, mo, mg, mu, md;
    const CUtensorMapSwizzle S128 = CU_TENSOR_MAP_SWIZZLE_128B, S64 = CU_TENSOR_MAP_SWIZZLE_64B;
    bool ok = true;
    ok &= make_map(enc, &mq, d_in[3], 2, 4096, 512, 1, 8192, 0, 64, 128, 1, S128);
    ok &= make_map(enc, &mk, d_in[1], 3, 64, 131072, 2, 256, 128, 64, 64, 2, S128);
    ok &= make_map(enc, &mv, d_in[2], 3, 64, 131072, 2, 256, 128, 64, 64, 2, S128);
    ok &= make_map(enc, &mo, d_in[4], 2, 512, 4096, 1, 1024, 0, 64, 128, 1, S128);
    ok &= make_map(enc, &mg, d_in[6], 3, 32, 512, 56, 3584, 64, 32, 16, 7, S64);
    ok &= make_map(enc, &mu, d_in[7], 3, 32, 512, 56, 3584, 64, 32, 16, 7, S64);
    ok &= make_map(enc, &md, d_in[8], 2, 512, 1792, 1, 1024, 0, 64, 112, 1, S128);
    if (!ok) return;
    const Ptrs ptrs = {(const bf16*)d_in[0], (bf16*)d_out, (uint32_t*)gy, (uint32_t*)ghh, (uint32_t*)gready, (const unsigned char*)d_in[3], (const unsigned char*)d_in[1],
                       (const unsigned char*)d_in[2], (const unsigned char*)d_in[4], (const unsigned char*)d_in[6], (const unsigned char*)d_in[7], (const unsigned char*)d_in[8]};
    fused_decode_kernel<<<NCTA, NTHREADS, SMEM_BYTES, cudaStreamPerThread>>>(ptrs, mq, mk, mv, mo, mg, mu, md);
}
```

```cpp
#include <cuda_runtime.h>
#include <cuda_bf16.h>
#include <cuda.h>
#include <stdint.h>

namespace {

typedef __nv_bfloat16 bf16;

constexpr int NCTA = 64;
constexpr int NCW = 16;
constexpr int NTHREADS = NCW * 32 + 96;
constexpr int NSLOT = 12;
constexpr int SLOT = 16384;
constexpr int NUNIT = 30;
constexpr int WINDOW = 10;
constexpr int PACE0_NS = 750;
constexpr int GU_GAP = 150;
constexpr int WD_GAP = 400;
constexpr int G1_DELAY = 250;

constexpr int OFF_XN = NSLOT * SLOT;
constexpr int OFF_Q = OFF_XN + 2112;
constexpr int OFF_QP = OFF_Q + 1088;
constexpr int OFF_S = OFF_QP + 4096;
constexpr int OFF_GIN = OFF_S;
constexpr int OFF_GST = OFF_GIN + 3584;
constexpr int OFF_SIN = OFF_GST + 128;
constexpr int OFF_P = OFF_S + 8192;
constexpr int OFF_RED = OFF_P + 4160;
constexpr int OFF_ML = OFF_RED + 128;
constexpr int OFF_OST = OFF_ML + 128;
constexpr int OFF_OA = OFF_OST + 1024;
constexpr int OFF_H = OFF_OA + 8704;
constexpr int OFF_OIN = OFF_H + 288;
constexpr int OFF_BAR = OFF_OIN + 1088;
constexpr int BAR_Q = 30, BAR_C = 31, BAR_Y = 32, BAR_G = 33, BAR_O = 34, BAR_S = 35, BAR_A = 36, BAR_X = 37, BAR_EMPTY = 40;
constexpr int SMEM_BYTES = OFF_BAR + 64 * 8;
static_assert(SMEM_BYTES <= 232448, "smem");
static_assert(OFF_SIN + 1792 <= OFF_P, "alias");
static_assert(OFF_OA % 16 == 0 && OFF_OST % 16 == 0 && OFF_ML % 16 == 0 && OFF_OIN % 16 == 0 && OFF_S % 16 == 0 && OFF_BAR % 8 == 0 && OFF_P % 16 == 0 && OFF_QP % 16 == 0, "align");
constexpr uint32_t EMPTY = 0xFFFFFFFFu;

__device__ __align__(128) uint32_t g_y[NCTA * 128];
__device__ __align__(128) uint32_t g_hh[NCTA * 32];
__device__ unsigned int g_ready;


__device__ __forceinline__ uint32_t smem_u32(const void* p) { return (uint32_t)__cvta_generic_to_shared(p); }
__device__ __forceinline__ void mbar_init(uint32_t bar, int cnt) { asm volatile("mbarrier.init.shared::cta.b64 [%0], %1;" ::"r"(bar), "r"(cnt) : "memory"); }
__device__ __forceinline__ void mbar_expect(uint32_t bar, uint32_t bytes) { asm volatile("mbarrier.arrive.expect_tx.shared::cta.b64 _, [%0], %1;" ::"r"(bar), "r"(bytes) : "memory"); }
__device__ __forceinline__ void mbar_arrive(uint32_t bar) { asm volatile("mbarrier.arrive.shared::cta.b64 _, [%0];" ::"r"(bar) : "memory"); }
__device__ __forceinline__ bool mbar_try(uint32_t bar) {
    uint32_t ok;
    asm volatile("{\n.reg .pred p;\nmbarrier.try_wait.parity.shared::cta.b64 p, [%1], 0;\nselp.u32 %0, 1, 0, p;\n}" : "=r"(ok) : "r"(bar) : "memory");
    return ok;
}
__device__ __forceinline__ void mbar_wait(uint32_t bar) {
    int it = 0;
    while (!mbar_try(bar)) { if (++it > (1 << 18)) __trap(); }
}
__device__ __forceinline__ void tma2d(uint32_t dst, const CUtensorMap* map, int c0, int c1, uint32_t bar, uint64_t pol) {
    asm volatile("cp.async.bulk.tensor.2d.shared::cluster.global.mbarrier::complete_tx::bytes.L2::cache_hint [%0], [%1, {%3, %4}], [%2], %5;"
                 ::"r"(dst), "l"(map), "r"(bar), "r"(c0), "r"(c1), "l"(pol) : "memory");
}
__device__ __forceinline__ void tma3d(uint32_t dst, const CUtensorMap* map, int c0, int c1, int c2, uint32_t bar, uint64_t pol) {
    asm volatile("cp.async.bulk.tensor.3d.shared::cluster.global.mbarrier::complete_tx::bytes.L2::cache_hint [%0], [%1, {%3, %4, %5}], [%2], %6;"
                 ::"r"(dst), "l"(map), "r"(bar), "r"(c0), "r"(c1), "r"(c2), "l"(pol) : "memory");
}
__device__ __forceinline__ void tmap_prefetch(const CUtensorMap* m) { asm volatile("prefetch.tensormap [%0];" ::"l"(m) : "memory"); }
__device__ __forceinline__ uint32_t mapa(uint32_t a, uint32_t rank) { uint32_t d; asm("mapa.shared::cluster.u32 %0, %1, %2;" : "=r"(d) : "r"(a), "r"(rank)); return d; }
__device__ __forceinline__ void st_async1(uint32_t a, uint32_t v, uint32_t bar) {
    asm volatile("st.async.weak.shared::cluster.mbarrier::complete_tx::bytes.b32 [%0], %1, [%2];" ::"r"(a), "r"(v), "r"(bar) : "memory");
}
__device__ __forceinline__ void st_async2(uint32_t a, float v0, float v1, uint32_t bar) {
    asm volatile("st.async.weak.shared::cluster.mbarrier::complete_tx::bytes.v2.f32 [%0], {%1, %2}, [%3];" ::"r"(a), "f"(v0), "f"(v1), "r"(bar) : "memory");
}
__device__ __forceinline__ void st_async4(uint32_t a, float v0, float v1, float v2, float v3, uint32_t bar) {
    asm volatile("st.async.weak.shared::cluster.mbarrier::complete_tx::bytes.v4.f32 [%0], {%1, %2, %3, %4}, [%5];" ::"r"(a), "f"(v0), "f"(v1), "f"(v2), "f"(v3), "r"(bar) : "memory");
}
__device__ __forceinline__ void ldsm4(uint32_t (&r)[4], uint32_t a) {
    asm volatile("ldmatrix.sync.aligned.m8n8.x4.shared.b16 {%0,%1,%2,%3}, [%4];" : "=r"(r[0]), "=r"(r[1]), "=r"(r[2]), "=r"(r[3]) : "r"(a) : "memory");
}
__device__ __forceinline__ void ldsm4t(uint32_t (&r)[4], uint32_t a) {
    asm volatile("ldmatrix.sync.aligned.m8n8.x4.trans.shared.b16 {%0,%1,%2,%3}, [%4];" : "=r"(r[0]), "=r"(r[1]), "=r"(r[2]), "=r"(r[3]) : "r"(a) : "memory");
}
__device__ __forceinline__ void mma(float (&c)[4], const uint32_t (&a)[4], uint32_t b0, uint32_t b1) {
    asm volatile("mma.sync.aligned.m16n8k16.row.col.f32.bf16.bf16.f32 {%0,%1,%2,%3}, {%4,%5,%6,%7}, {%8,%9}, {%0,%1,%2,%3};"
                 : "+f"(c[0]), "+f"(c[1]), "+f"(c[2]), "+f"(c[3]) : "r"(a[0]), "r"(a[1]), "r"(a[2]), "r"(a[3]), "r"(b0), "r"(b1));
}
__device__ __forceinline__ uint32_t lds32(uint32_t a) { uint32_t v; asm volatile("ld.shared.b32 %0, [%1];" : "=r"(v) : "r"(a) : "memory"); return v; }
__device__ __forceinline__ float ldsf(uint32_t a) { float v; asm volatile("ld.shared.f32 %0, [%1];" : "=f"(v) : "r"(a) : "memory"); return v; }
__device__ __forceinline__ float2 ldsf2(uint32_t a) { float2 v; asm volatile("ld.shared.v2.f32 {%0,%1}, [%2];" : "=f"(v.x), "=f"(v.y) : "r"(a) : "memory"); return v; }
__device__ __forceinline__ float4 ldsf4(uint32_t a) { float4 v; asm volatile("ld.shared.v4.f32 {%0,%1,%2,%3}, [%4];" : "=f"(v.x), "=f"(v.y), "=f"(v.z), "=f"(v.w) : "r"(a) : "memory"); return v; }
__device__ __forceinline__ uint4 lds128(uint32_t a) { uint4 v; asm volatile("ld.shared.v4.b32 {%0,%1,%2,%3}, [%4];" : "=r"(v.x), "=r"(v.y), "=r"(v.z), "=r"(v.w) : "r"(a) : "memory"); return v; }
__device__ __forceinline__ void lds128p(uint4& v, uint32_t a, uint32_t p) {
    asm volatile("{\n.reg .pred q;\nsetp.ne.u32 q, %5, 0;\n@q ld.shared.v4.b32 {%0,%1,%2,%3}, [%4];\n}" : "+r"(v.x), "+r"(v.y), "+r"(v.z), "+r"(v.w) : "r"(a), "r"(p) : "memory");
}
__device__ __forceinline__ void sts32(uint32_t a, uint32_t v) { asm volatile("st.shared.b32 [%0], %1;" ::"r"(a), "r"(v) : "memory"); }
__device__ __forceinline__ int bperm(int k) { return (k & ~31) + 8 * ((k & 7) >> 1) + 4 * ((k >> 4) & 1) + 2 * ((k >> 3) & 1) + (k & 1); }
__device__ __forceinline__ void stsf(uint32_t a, float v) { asm volatile("st.shared.f32 [%0], %1;" ::"r"(a), "f"(v) : "memory"); }
__device__ __forceinline__ void stsf2(uint32_t a, float v0, float v1) { asm volatile("st.shared.v2.f32 [%0], {%1,%2};" ::"r"(a), "f"(v0), "f"(v1) : "memory"); }
__device__ __forceinline__ void sts64(uint32_t a, uint32_t v0, uint32_t v1) { asm volatile("st.shared.v2.b32 [%0], {%1,%2};" ::"r"(a), "r"(v0), "r"(v1) : "memory"); }
__device__ __forceinline__ void sts16(uint32_t a, uint16_t v) { asm volatile("st.shared.b16 [%0], %1;" ::"r"(a), "h"(v) : "memory"); }
__device__ __forceinline__ uint32_t ldg_acq(const uint32_t* p) { uint32_t v; asm volatile("ld.acquire.gpu.global.b32 %0, [%1];" : "=r"(v) : "l"(p) : "memory"); return v; }
__device__ __forceinline__ uint2 ldg_rlx2(const uint32_t* p) { uint2 v; asm volatile("ld.relaxed.gpu.global.v2.b32 {%0,%1}, [%2];" : "=r"(v.x), "=r"(v.y) : "l"(p) : "memory"); return v; }
__device__ __forceinline__ uint4 ldg_rlx4(const uint32_t* p) { uint4 v; asm volatile("ld.relaxed.gpu.global.v4.b32 {%0,%1,%2,%3}, [%4];" : "=r"(v.x), "=r"(v.y), "=r"(v.z), "=r"(v.w) : "l"(p) : "memory"); return v; }
__device__ __forceinline__ void stg_rlx(uint32_t* p, uint32_t v) { asm volatile("st.relaxed.gpu.global.b32 [%0], %1;" ::"l"(p), "r"(v) : "memory"); }
__device__ __forceinline__ void stg_rlx2(uint32_t* p, uint32_t a, uint32_t b) { asm volatile("st.relaxed.gpu.global.v2.b32 [%0], {%1,%2};" ::"l"(p), "r"(a), "r"(b) : "memory"); }
__device__ __forceinline__ void bar_compute() { asm volatile("bar.sync 1, 512;" ::: "memory"); }

__device__ __forceinline__ float bfr(float v) { uint32_t d; asm("cvt.rn.bf16x2.f32 %0, %1, %2;" : "=r"(d) : "f"(v), "f"(0.f)); return __uint_as_float(d); }
__device__ __forceinline__ uint32_t pack2(float lo, float hi) { uint32_t d; asm("cvt.rn.bf16x2.f32 %0, %1, %2;" : "=r"(d) : "f"(hi), "f"(lo)); return d; }
__device__ __forceinline__ float bf_lo(uint32_t v) { return __uint_as_float(v << 16); }
__device__ __forceinline__ float bf_hi(uint32_t v) { return __uint_as_float(v & 0xffff0000u); }
__device__ __forceinline__ float fsel(bool p, float a, float b) { float d; asm("{\n.reg .pred q;\nsetp.ne.u32 q, %3, 0;\nselp.f32 %0, %1, %2, q;\n}" : "=f"(d) : "f"(a), "f"(b), "r"((uint32_t)p)); return d; }
__device__ __forceinline__ float rcp(float x) { float y; asm("rcp.approx.ftz.f32 %0, %1;" : "=f"(y) : "f"(x)); return y; }
__device__ __forceinline__ float ex2(float x) { float y; asm("ex2.approx.ftz.f32 %0, %1;" : "=f"(y) : "f"(x)); return y; }
__device__ __forceinline__ uint32_t pin(uint32_t v) { asm volatile("" : "+r"(v)); return v; }
template <class T> __device__ __forceinline__ T* pinp(T* v) { asm volatile("" : "+l"(v)); return v; }
__device__ __forceinline__ bool elect_one() { uint32_t p; asm volatile("{\n.reg .pred q;\nelect.sync _|q, 0xffffffff;\nselp.u32 %0, 1, 0, q;\n}" : "=r"(p)); return p; }
__device__ __forceinline__ void spin(int cycles) { const int c0 = (int)clock(); while ((int)clock() - c0 < cycles) { } }
__device__ __forceinline__ unsigned int now_ns() { unsigned int t; asm volatile("mov.u32 %0, %%globaltimer_lo;" : "=r"(t)); return t; }
__device__ __forceinline__ float ln_rstd(float m2) {
    float sq;
    asm("sqrt.approx.ftz.f32 %0, %1;" : "=f"(sq) : "f"(bfr(bfr(m2 * (1.f / 512.f)) + 1e-5f)));
    return rcp(bfr(sq));
}
#define SUM8(v, f) (((v[0] f + v[1] f) + (v[2] f + v[3] f)) + ((v[4] f + v[5] f) + (v[6] f + v[7] f)))

struct Ptrs { const bf16* x; bf16* out; uint32_t *gy, *ghh, *ready; const unsigned char *wq, *k, *v, *wo, *wg, *wu, *wd; unsigned int pace; };

__global__ void __cluster_dims__(8, 1, 1) __launch_bounds__(NTHREADS, 1)
fused_decode_kernel(const Ptrs ptrs, const __grid_constant__ CUtensorMap mq, const __grid_constant__ CUtensorMap mk,
                    const __grid_constant__ CUtensorMap mv, const __grid_constant__ CUtensorMap mo, const __grid_constant__ CUtensorMap mg,
                    const __grid_constant__ CUtensorMap mu, const __grid_constant__ CUtensorMap md) {
    extern __shared__ __align__(1024) unsigned char smem_raw[];
    const uint32_t sb = smem_u32(smem_raw);
    const int tid = threadIdx.x, warp = __shfl_sync(~0u, tid >> 5, 0), lane = tid & 31;
    const int c = blockIdx.x >> 3;
    const int r = blockIdx.x & 7;
    const uint32_t bars = sb + OFF_BAR;
#define WAIT(b) mbar_wait(bars + 8 * (b))
#define ARRIVE(b) do { __syncwarp(); if (lane == 0) mbar_arrive(bars + 8 * (b)); } while (0)

    uint64_t pol;
    asm volatile("createpolicy.fractional.L2::evict_first.b64 %0, 1.0;" : "=l"(pol));
    const unsigned int tg0 = now_ns();
    if (tid == NCW * 32) {
        tmap_prefetch(&mq);
#pragma unroll
        for (int i = 0; i < 2; i++)
            asm volatile("cp.async.bulk.prefetch.L2.global.L2::cache_hint [%0], %1, %2;" ::"l"(ptrs.wq + i * 1048576 + blockIdx.x * 16384), "r"(16384), "l"(pol) : "memory");
#pragma unroll
        for (int u = 0; u < 4; u++) {
            mbar_init(bars + 8 * u, 1);
            mbar_expect(bars + 8 * u, SLOT);
            tma2d(sb + u * SLOT, &mq, c * 512 + r * 64, u * 128, bars + 8 * u, pol);
        }
    }
    if (warp == NCW + 2 && lane < 6) {
        const size_t kvoff = (size_t)(((r >> 2) * 8 + c) * 8192 + 6144 + (r & 3) * 64) * 256;
        const unsigned char* p = lane == 0 ? ptrs.k + kvoff : lane == 1 ? ptrs.v + kvoff : lane == 2 ? ptrs.wo + (size_t)c * 512 * 1024 + r * 128
                               : lane == 3 ? ptrs.wg + (size_t)r * 64 * 3584 + c * 448 : lane == 4 ? ptrs.wu + (size_t)r * 64 * 3584 + c * 448
                               : ptrs.wd + (size_t)r * 224 * 1024 + c * 128;
        asm volatile("prefetch.global.L2 [%0];" ::"l"(p) : "memory");
    }
    uint4 v0 = make_uint4(0u, 0u, 0u, 0u), v1 = v0;
    asm volatile("{\n.reg .pred p;\nsetp.ne.u32 p, %9, 0;\n@p ld.global.nc.v4.u32 {%0,%1,%2,%3}, [%8];\n@p ld.global.nc.v4.u32 {%4,%5,%6,%7}, [%8+512];\n}"
                 : "+r"(v0.x), "+r"(v0.y), "+r"(v0.z), "+r"(v0.w), "+r"(v1.x), "+r"(v1.y), "+r"(v1.z), "+r"(v1.w)
                 : "l"(ptrs.x + (warp & 1) * 512 + lane * 8), "r"((uint32_t)(warp < 2)));
    if (warp == NCW + 1 || warp == NCW + 2) {
        stg_rlx2(ptrs.gy + blockIdx.x * 128 + (tid - (NCW + 1) * 32) * 2, EMPTY, EMPTY);
        if (lane < 16) stg_rlx(ptrs.ghh + blockIdx.x * 32 + (warp - NCW - 1) * 16 + lane, EMPTY);
        if (tid == (NCW + 1) * 32) tmap_prefetch(&mk);
    }
    if (warp >= 2 && warp < 14 && elect_one()) {
        const int j = warp - 2;
        const uint32_t b = bars + 8 * (4 + j);
        mbar_init(b, 1);
        mbar_init(b + 8 * 12, 1);
        mbar_init(b + 8 * 24, j == BAR_X - 28 ? 2 : 1);
        mbar_init(b + 8 * 36, j < 4 ? NCW : 4);
        if (j < 6) mbar_init(b + 8 * 48, 8);
        if (j >= 2 && j < 9 && j != 4) mbar_expect(b + 8 * 24, j == 2 ? 1024u : j == 3 ? 128u : j == 5 ? 3712u : j == 6 ? 1088u : j == 7 ? 1792u : 8192u);
    }
    asm volatile("fence.mbarrier_init.release.cluster;" ::: "memory");
    __syncthreads();
    asm volatile("barrier.cluster.arrive.relaxed.aligned;" ::: "memory");

    if (warp < 2) {
        const uint32_t xw[8] = {v0.x, v0.y, v0.z, v0.w, v1.x, v1.y, v1.z, v1.w};
        float f[16], s = 0.f;
#pragma unroll
        for (int i = 0; i < 8; i++) { f[2 * i] = bf_lo(xw[i]); f[2 * i + 1] = bf_hi(xw[i]); s += f[2 * i] + f[2 * i + 1]; }
#pragma unroll
        for (int o = 16; o; o >>= 1) s += __shfl_xor_sync(~0u, s, o);
        const float mean = s * (1.f / 512.f);
        float q = 0.f;
#pragma unroll
        for (int i = 0; i < 16; i++) { const float d = f[i] - mean; q += d * d; }
#pragma unroll
        for (int o = 16; o; o >>= 1) q += __shfl_xor_sync(~0u, q, o);
        const float mb = bfr(mean), rd = ln_rstd(q);
        uint32_t o8[8];
#pragma unroll
        for (int i = 0; i < 8; i++) o8[i] = pack2(bfr(f[2 * i] - mb) * rd, bfr(f[2 * i + 1] - mb) * rd);
        const uint32_t xd = sb + OFF_XN + warp * 1040 + bperm(lane * 8) * 2;
#pragma unroll
        for (int i = 0; i < 8; i++) sts32(xd + (i >> 2) * 512 + (i & 3) * 16, o8[i]);
        ARRIVE(BAR_X);
    }
    const int g = lane >> 2, t = lane & 3;

    if (warp == NCW) {
        if (lane == 0) {
            const int kvrow = ((r >> 2) * 8 + c) * 8192 + 6144 + (r & 3) * 64;
            const int rot = c * 3 + (r >> 2) * 4;
            const unsigned int pace = ptrs.pace;
            unsigned int due = tg0 + PACE0_NS + (pace * blockIdx.x) / 64;
#pragma unroll 1
            for (int u = 4; u < NUNIT; u++) {
                const int slot = u >= 24 ? u - 24 : u >= 12 ? u - 12 : u;
                const uint32_t dst = sb + slot * SLOT, fb = bars + 8 * u;
                if (u >= NSLOT) WAIT(BAR_EMPTY + u - NSLOT);
                if (u >= WINDOW) WAIT(u - WINDOW);
                if (u == 28) {
                    WAIT(BAR_Y);
                    due = now_ns() + WD_GAP;
                }
                while ((int)(now_ns() - due) < 0) { }
                due += u >= 28 ? 0 : u >= 24 ? pace * 7 / 8 : u == 23 ? pace + GU_GAP : pace;
                if (u < 12) { mbar_expect(fb, SLOT); tma3d(dst, &mk, 0, kvrow + ((u - 4 + rot) & 7) * 256, 0, fb, pol); }
                else if (u < 20) { mbar_expect(fb, SLOT); tma3d(dst, &mv, 0, kvrow + ((u - 12 + rot) & 7) * 256, 0, fb, pol); }
                else if (u < 24) { mbar_expect(fb, SLOT); tma2d(dst, &mo, r * 64, c * 512 + (u - 20) * 128, fb, pol); }
                else if (u < 28) {
                    mbar_expect(fb, 14336);
                    tma3d(dst, &mg, 0, r * 64 + (u - 24) * 16, c * 7, fb, pol);
                    tma3d(dst + 8192, &mu, 0, r * 64 + (u - 24) * 16, c * 7, fb, pol);
                } else { mbar_expect(fb, 14336); tma2d(dst, &md, c * 64, r * 224 + (u - 28) * 112, fb, pol); }
            }
        }
        return;
    }
    if (warp > NCW) {
        const int b = warp - NCW - 1, e = b * 32 + lane;
        if (b == 0) {
            if (lane == 1) tmap_prefetch(&mv);
            if (lane == 2) tmap_prefetch(&mo);
            if (lane == 3) tmap_prefetch(&mg);
            if (lane == 4) tmap_prefetch(&mu);
            if (lane == 5) tmap_prefetch(&md);
        }
        const float x0 = __bfloat162float(ptrs.x[r * 64 + e]), x1 = __bfloat162float(ptrs.x[512 + r * 64 + e]);
        asm volatile("fence.acq_rel.gpu;" ::: "memory");
        __syncwarp();
        if (lane == 0) {
            asm volatile("red.relaxed.gpu.global.add.u32 [%0], 1;" ::"l"(ptrs.ready) : "memory");
            int it = 0;
            while (ldg_acq(ptrs.ready) < 2u * NCTA) { __nanosleep(500); if (++it > (1 << 18)) __trap(); }
        }
        __syncwarp();
        asm volatile("barrier.cluster.wait.aligned;" ::: "memory");
        {
            uint32_t* ypub = pinp(ptrs.gy + blockIdx.x * 128 + e * 2);
            const uint32_t* src = pinp(ptrs.gy + r * 128 + e * 2);
            const uint32_t yin = pin(sb + OFF_QP + e * 8), hdst = pin(sb + OFF_H + bperm(e) * 2), boff = pin(sb + OFF_H + (g & 1) * 144 + t * 16);
            const int srk = (g >> 1) * 2 + (t >> 1);
            const uint32_t sdst = pin(mapa(sb + OFF_GST + r * 16 + (g & 1) * 8 + ((t & 1) ? 0 : 4), srk)), sbar = pin(mapa(bars + 8 * BAR_G, srk));
            asm volatile("bar.sync 3, 576;" ::: "memory");
            {
                float2 p[8];
#pragma unroll
                for (int s = 0; s < 8; s++) p[s] = ldsf2(yin + s * 512);
                stg_rlx2(ypub, __float_as_uint(SUM8(p, .x)), __float_as_uint(SUM8(p, .y)));
            }
            if (tid == (NCW + 1) * 32) mbar_arrive(bars + 8 * BAR_Y);
            float y0, y1;
            spin(G1_DELAY);
            for (int it = 0;; it++) {
                float2 v[8];
#pragma unroll
                for (int s = 0; s < 8; s++) { const uint2 u = ldg_rlx2(src + s * 1024); v[s] = make_float2(__uint_as_float(u.x), __uint_as_float(u.y)); }
                y0 = SUM8(v, .x);
                y1 = SUM8(v, .y);
                if (!__any_sync(~0u, (y0 + y1) != (y0 + y1))) break;
                if (it > 64) {
                    uint32_t mx = 0u;
#pragma unroll
                    for (int s = 0; s < 8; s++) mx = max(mx, max(__float_as_uint(v[s].x), __float_as_uint(v[s].y)));
                    if (!__any_sync(~0u, mx == EMPTY)) break;
                    if (it > (1 << 20)) __trap();
                }
            }
            const uint32_t hp = pack2(x0 + bfr(y0), x1 + bfr(y1));
            sts16(hdst, (uint16_t)hp);
            sts16(hdst + 144, (uint16_t)(hp >> 16));
            asm volatile("bar.sync 2, 512;" ::: "memory");
            const uint4 h0 = lds128(boff), h1 = lds128(boff + 64);
            const uint32_t hf[8] = {h0.x, h0.y, h0.z, h0.w, h1.x, h1.y, h1.z, h1.w};
            float sa[4][4];
#pragma unroll
            for (int i = 0; i < 4; i++) {
                const uint32_t a[4] = {hf[2 * i], 0u, hf[2 * i + 1], 0u};
                const uint32_t b0 = (g & 2) ? 0x3F803F80u : hf[2 * i], b1 = (g & 2) ? 0x3F803F80u : hf[2 * i + 1];
                sa[i][0] = sa[i][1] = sa[i][2] = sa[i][3] = 0.f;
                mma(sa[i], a, b0, b1);
            }
            const float sv = fsel((g & 1) && !(t & 1), (sa[0][1] + sa[1][1]) + (sa[2][1] + sa[3][1]), (sa[0][0] + sa[1][0]) + (sa[2][0] + sa[3][0]));
            if ((g & 1) == b) st_async1(sdst, __float_as_uint(sv), sbar);
            if (r == c) {
                const int hr = 2 * (e >> 4) + ((e >> 2) & 1);
                st_async2(mapa(sb + OFF_OIN + 1024 + (e & 3) * 16 + (e & 8), hr), bf_lo(hp), bf_hi(hp), mapa(bars + 8 * BAR_O, hr));
            }
        }
        {
            const int lc = lane < 28 ? lane : 27;
            uint32_t* hpub = pinp(ptrs.ghh + blockIdx.x * 32 + b * 16 + ((lane >> 1) & 3) * 4 + (lane >> 3));
            const uint32_t gst = pin(sb + OFF_GST + b * 8), gin = pin(sb + OFF_GIN + lc * 16 + b * 8);
            float2 st[8], v[8];
            WAIT(BAR_S);
#pragma unroll
            for (int s = 0; s < 8; s++) v[s] = ldsf2(sb + OFF_SIN + s * 224 + lc * 8);
            const float gs = SUM8(v, .x), us = SUM8(v, .y);
            WAIT(BAR_G);
#pragma unroll
            for (int s = 0; s < 8; s++) st[s] = ldsf2(gst + s * 16);
#pragma unroll
            for (int s = 0; s < 8; s++) v[s] = ldsf2(gin + s * 448);
            const float mu = SUM8(st, .x) * (1.f / 512.f);
            const float rs = ln_rstd(fmaxf(fmaf(-512.f * mu, mu, SUM8(st, .y)), 0.f)), mb = bfr(mu);
            const float ga = bfr(fmaf(-mb, gs, SUM8(v, .x)) * rs), ua = bfr(fmaf(-mb, us, SUM8(v, .y)) * rs);
            const float K2 = -2.f * 0.7978845608028654f * 1.4426950408889634f;
            const float ea = ex2(ga * fmaf(K2 * 0.044715f * ga, ga, K2));
            const float ha = bfr(ga * rcp(1.f + ea)) * ua;
            const uint32_t wd = pack2(ha, __shfl_down_sync(~0u, ha, 1));
            if (!(lane & 1)) stg_rlx(hpub, lane < 28 ? wd : 0u);
        }
        if (b == 0) {
            const int l = lane & 15;
            bf16* dsto = pinp(ptrs.out + (l & 1) * 512 + c * 64 + (r >> 1) * 16 + (r & 1) * 4 + (l >> 2) + (l & 2) * 4);
            const uint32_t oin = pin(sb + OFF_OIN + l * 4);
            WAIT(BAR_O);
            float p[8], q[8];
#pragma unroll
            for (int s = 0; s < 8; s++) { p[s] = ldsf(oin + s * 64); q[s] = ldsf(oin + 512 + s * 64); }
            const float hf = ldsf(oin + 1024);
            if (lane < 16) *reinterpret_cast<uint16_t*>(dsto) = (uint16_t)pack2(hf + bfr(SUM8(p, ) + SUM8(q, )), 0.f);
            if (blockIdx.x == 0 && lane == 16) stg_rlx(ptrs.ready, 0u);
        }
        return;
    }

    const int w = warp;
    const int lrow = lane & 7, lm1 = (lane >> 3) & 1, lm2 = lane >> 4;
    const float L2E = 1.4426950408889634f;
    const uint32_t gv_a = sb + (uint32_t)(((w >> 2) * 32 + lrow + 8 * lm2) * 128 + (((2 * (w & 3) + lm1) ^ lrow) << 4));
    const uint32_t gv_b = sb + OFF_XN + (g & 1) * 1040 + (w >> 2) * 64 + t * 16;
    const uint32_t gv_d = pin(sb + OFF_QP + ((w >> 2) * 64 + (w & 3) * 16 + g) * 8);
    const uint32_t blane = lane < 8;
    {
        WAIT(BAR_X);
        float acc0[4] = {0.f, 0.f, 0.f, 0.f}, acc1[4] = {0.f, 0.f, 0.f, 0.f};
        uint4 bq = make_uint4(0u, 0u, 0u, 0u);
#pragma unroll 1
        for (int u = 0; u < 4; u++) {
            lds128p(bq, gv_b + u * 256, blane);
            WAIT(u);
            uint32_t a0[4], a1[4];
            ldsm4t(a0, gv_a + u * SLOT);
            ldsm4t(a1, gv_a + u * SLOT + 2048);
            mma(acc0, a0, bq.x, bq.y);
            mma(acc1, a1, bq.z, bq.w);
            ARRIVE(BAR_EMPTY + u);
        }
        if (t == 0) { stsf2(gv_d, acc0[0] + acc1[0], acc0[1] + acc1[1]); stsf2(gv_d + 64, acc0[2] + acc1[2], acc0[3] + acc1[3]); }
        asm volatile("barrier.cluster.wait.aligned;" ::: "memory");
        bar_compute();
        if (tid < 32) {
            float s[4] = {0.f, 0.f, 0.f, 0.f};
#pragma unroll
            for (int k = 0; k < 4; k++) { const float4 v = ldsf4(sb + OFF_QP + k * 512 + lane * 16); s[0] += v.x; s[1] += v.y; s[2] += v.z; s[3] += v.w; }
            const uint32_t w0 = pack2(s[0], s[2]), w1 = pack2(s[1], s[3]);
            const uint32_t dst = sb + OFF_Q + (r >> 1) * 272 + ((r & 1) * 64 + lane * 2) * 2;
#pragma unroll
            for (int j = 0; j < 8; j++) st_async1(mapa(dst, j), j < 4 ? w0 : w1, mapa(bars + 8 * BAR_Q, j));
        }
    }
    {
        WAIT(BAR_Q);
        uint32_t qf[16];
#pragma unroll
        for (int ks = 0; ks < 8; ks++) {
            const uint32_t a = sb + OFF_Q + (g & 3) * 272 + (ks * 16 + 2 * t) * 2;
            qf[2 * ks] = lds32(a); qf[2 * ks + 1] = lds32(a + 16);
        }
        const int mt = w & 3;
#pragma unroll 1
        for (int j = w >> 2; j < 8; j += 4) {
            WAIT(4 + j);
            float acc0[4] = {0.f, 0.f, 0.f, 0.f}, acc1[4] = {0.f, 0.f, 0.f, 0.f};
            const uint32_t base = sb + (4 + j) * SLOT + (uint32_t)((mt * 16 + lrow + 8 * lm1) * 128);
#pragma unroll
            for (int ks = 0; ks < 4; ks++) {
                uint32_t a0[4], a1[4];
                const uint32_t sw = (uint32_t)(((2 * ks + lm2) ^ lrow) << 4);
                ldsm4(a0, base + sw);
                ldsm4(a1, base + 8192 + sw);
                mma(acc0, a0, qf[2 * ks], qf[2 * ks + 1]);
                mma(acc1, a1, qf[8 + 2 * ks], qf[8 + 2 * ks + 1]);
            }
            ARRIVE(BAR_EMPTY + 4 + j);
            const float sc = 0.08838834764831845f;
            const bool hi = t >> 1;
            const uint32_t p = sb + OFF_S + (2 * (t & 1) * 512 + j * 64 + mt * 16 + g + 8 * (t >> 1)) * 4;
            stsf(p, bfr(bfr(fsel(hi, acc0[2] + acc1[2], acc0[0] + acc1[0])) * sc));
            stsf(p + 2048, bfr(bfr(fsel(hi, acc0[3] + acc1[3], acc0[1] + acc1[1])) * sc));
        }
        bar_compute();
    }
    {
        const int h = w >> 2;
        const float4 s = ldsf4(sb + OFF_S + tid * 16);
        float m = fmaxf(fmaxf(s.x, s.y), fmaxf(s.z, s.w));
#pragma unroll
        for (int o = 16; o; o >>= 1) m = fmaxf(m, __shfl_xor_sync(~0u, m, o));
        if (lane == 0) stsf(sb + OFF_RED + w * 4, m);
        bar_compute();
        const float4 mm = ldsf4(sb + OFF_RED + h * 16);
        m = fmaxf(fmaxf(mm.x, mm.y), fmaxf(mm.z, mm.w));
        const float p0 = ex2((s.x - m) * L2E), p1 = ex2((s.y - m) * L2E), p2 = ex2((s.z - m) * L2E), p3 = ex2((s.w - m) * L2E);
        sts64(sb + OFF_P + h * 1040 + (tid & 127) * 8, pack2(p0, p1), pack2(p2, p3));
        float l = (p0 + p1) + (p2 + p3);
#pragma unroll
        for (int o = 16; o; o >>= 1) l += __shfl_xor_sync(~0u, l, o);
        if (lane == 0) stsf(sb + OFF_RED + 64 + w * 4, l);
        bar_compute();
        if (tid < 16) {
            const int hh = tid & 3, rk = (r & 4) + (tid >> 2);
            const float4 a = ldsf4(sb + OFF_RED + hh * 16), b = ldsf4(sb + OFF_RED + 64 + hh * 16);
            st_async2(mapa(sb + OFF_ML + (r & 3) * 32 + hh * 8, rk), fmaxf(fmaxf(a.x, a.y), fmaxf(a.z, a.w)), (b.x + b.y) + (b.z + b.w), mapa(bars + 8 * BAR_C, rk));
        }
    }
    {
        const uint32_t dst = pin(mapa(sb + OFF_OA + r * 1088 + (tid & 63) * 16, tid >> 6)), dbar = pin(mapa(bars + 8 * BAR_A, tid >> 6));
        const uint32_t orr = pin(sb + OFF_OST + (tid & 63) * 16);
        if (w < 8) {
            float acc0[4] = {0.f, 0.f, 0.f, 0.f}, acc1[4] = {0.f, 0.f, 0.f, 0.f};
            const uint32_t aoff = sb + (uint32_t)((w >> 2) * 8192 + (lrow + 8 * lm2) * 128 + (((2 * (w & 3) + lm1) ^ lrow) << 4));
            const uint32_t boff = sb + OFF_P + (g & 3) * 1040 + t * 4;
            const int hi = t >> 1;
            const uint32_t ow = pin(sb + OFF_OST + (2 * (t & 1) * 128 + bperm(w * 16 + g + 8 * hi)) * 2);
            float f0, f1;
            {
                WAIT(BAR_C);
                const uint32_t ml = sb + OFF_ML + (t & 1) * 16;
                const float4 a = ldsf4(ml), b = ldsf4(ml + 32), cc = ldsf4(ml + 64), d = ldsf4(ml + 96), own = ldsf4(ml + (r & 3) * 32);
                const float M0 = fmaxf(fmaxf(a.x, b.x), fmaxf(cc.x, d.x)), M1 = fmaxf(fmaxf(a.z, b.z), fmaxf(cc.z, d.z));
                const float L0 = (ex2((a.x - M0) * L2E) * a.y + ex2((b.x - M0) * L2E) * b.y) + (ex2((cc.x - M0) * L2E) * cc.y + ex2((d.x - M0) * L2E) * d.y);
                const float L1 = (ex2((a.z - M1) * L2E) * a.w + ex2((b.z - M1) * L2E) * b.w) + (ex2((cc.z - M1) * L2E) * cc.w + ex2((d.z - M1) * L2E) * d.w);
                f0 = ex2((own.x - M0) * L2E) * rcp(L0);
                f1 = ex2((own.z - M1) * L2E) * rcp(L1);
            }
#pragma unroll 1
            for (int j = 0; j < 8; j++) {
                uint32_t pb[8];
#pragma unroll
                for (int i = 0; i < 8; i++) pb[i] = lds32(boff + j * 128 + i * 16);
                WAIT(12 + j);
                uint32_t a0[4], a1[4], a2[4], a3[4];
                ldsm4t(a0, aoff + j * SLOT);
                ldsm4t(a1, aoff + j * SLOT + 2048);
                ldsm4t(a2, aoff + j * SLOT + 4096);
                ldsm4t(a3, aoff + j * SLOT + 6144);
                mma(acc0, a0, pb[0], pb[1]);
                mma(acc1, a1, pb[2], pb[3]);
                mma(acc0, a2, pb[4], pb[5]);
                mma(acc1, a3, pb[6], pb[7]);
                if (j < 6) ARRIVE(BAR_EMPTY + 12 + j);
            }
            const uint32_t ob = pack2(fsel(hi, acc0[2] + acc1[2], acc0[0] + acc1[0]) * f0, fsel(hi, acc0[3] + acc1[3], acc0[1] + acc1[1]) * f1);
            sts16(ow, (uint16_t)ob);
            sts16(ow + 256, (uint16_t)(ob >> 16));
        }
        bar_compute();
        const uint4 oc = lds128(orr);
        st_async4(dst, __uint_as_float(oc.x), __uint_as_float(oc.y), __uint_as_float(oc.z), __uint_as_float(oc.w), dbar);
    }
    {
        uint32_t a[8][4];
        uint4 bq[4];
        const uint32_t ob = pin(sb + OFF_OA + g * 1088 + (w >> 2) * 64 + t * 16);
        const uint32_t yd = pin(sb + OFF_QP + (((w >> 2) * 2 + (t & 1)) * 64 + (w & 3) * 16 + g) * 8 + (t >> 1) * 4);
#pragma unroll
        for (int u = 0; u < 3; u++) {
            WAIT(20 + u);
            ldsm4t(a[2 * u], gv_a + (8 + u) * SLOT);
            ldsm4t(a[2 * u + 1], gv_a + (8 + u) * SLOT + 2048);
        }
        WAIT(BAR_A);
#pragma unroll
        for (int u = 0; u < 4; u++) bq[u] = lds128(ob + u * 256);
        float c0[4] = {0.f, 0.f, 0.f, 0.f}, c1[4] = {0.f, 0.f, 0.f, 0.f}, c2[4] = {0.f, 0.f, 0.f, 0.f}, c3[4] = {0.f, 0.f, 0.f, 0.f};
        mma(c0, a[0], bq[0].x, bq[0].y); mma(c1, a[1], bq[0].z, bq[0].w);
        mma(c2, a[2], bq[1].x, bq[1].y); mma(c3, a[3], bq[1].z, bq[1].w);
        mma(c0, a[4], bq[2].x, bq[2].y); mma(c1, a[5], bq[2].z, bq[2].w);
        WAIT(23);
        ldsm4t(a[6], gv_a + 11 * SLOT);
        ldsm4t(a[7], gv_a + 11 * SLOT + 2048);
#pragma unroll
        for (int i = 0; i < 4; i++) c0[i] += c1[i];
        mma(c2, a[6], bq[3].x, bq[3].y);
        mma(c3, a[7], bq[3].z, bq[3].w);
        stsf(yd, (c0[0] + c0[1]) + ((c2[0] + c3[0]) + (c2[1] + c3[1])));
        stsf(yd + 64, (c0[2] + c0[3]) + ((c2[2] + c3[2]) + (c2[3] + c3[3])));
    }
    asm volatile("bar.arrive 3, 576;" ::: "memory");
    if (w >= 14) return;
    {
        uint32_t ag[4][4], au[4][4];
        const int row = lrow + 8 * lm2;
        const uint32_t aoff = sb + (uint32_t)((w >> 1) * 1024 + row * 64 + (((2 * (w & 1) + lm1) ^ ((row >> 1) & 3)) << 4));
        const int col = w * 16 + g, rk0 = col / 28, lc0 = col - rk0 * 28, rk1 = (col + 8) / 28, lc1 = col + 8 - rk1 * 28;
        const uint32_t dst0 = pin(mapa(sb + OFF_GIN + r * 448 + lc0 * 16, rk0)), dbar0 = pin(mapa(bars + 8 * BAR_G, rk0));
        const uint32_t dst1 = pin(mapa(sb + OFF_GIN + r * 448 + lc1 * 16, rk1)), dbar1 = pin(mapa(bars + 8 * BAR_G, rk1));
        float sg[4] = {0.f, 0.f, 0.f, 0.f}, su[4] = {0.f, 0.f, 0.f, 0.f};
#pragma unroll
        for (int j = 0; j < 4; j++) {
            WAIT(24 + j);
            ldsm4t(ag[j], aoff + j * SLOT);
            ldsm4t(au[j], aoff + j * SLOT + 8192);
            mma(sg, ag[j], 0x3F803F80u, 0x3F803F80u);
            mma(su, au[j], 0x3F803F80u, 0x3F803F80u);
        }
        if (t == 0) {
            st_async2(mapa(sb + OFF_SIN + r * 224 + lc0 * 8, rk0), sg[0], su[0], mapa(bars + 8 * BAR_S, rk0));
            st_async2(mapa(sb + OFF_SIN + r * 224 + lc1 * 8, rk1), sg[2], su[2], mapa(bars + 8 * BAR_S, rk1));
        }
        const uint32_t boff = pin(sb + OFF_H + (g & 1) * 144 + t * 16);
        uint4 h0 = make_uint4(0u, 0u, 0u, 0u), h1 = h0;
        asm volatile("bar.sync 2, 512;" ::: "memory");
        lds128p(h0, boff, blane);
        lds128p(h1, boff + 64, blane);
        float g0[4] = {0.f, 0.f, 0.f, 0.f}, u0[4] = {0.f, 0.f, 0.f, 0.f}, g1[4] = {0.f, 0.f, 0.f, 0.f}, u1[4] = {0.f, 0.f, 0.f, 0.f};
        mma(g0, ag[0], h0.x, h0.y); mma(u0, au[0], h0.x, h0.y);
        mma(g1, ag[1], h0.z, h0.w); mma(u1, au[1], h0.z, h0.w);
        mma(g0, ag[2], h1.x, h1.y); mma(u0, au[2], h1.x, h1.y);
        mma(g1, ag[3], h1.z, h1.w); mma(u1, au[3], h1.z, h1.w);
        {
            const float e0 = g0[0] + g1[0], e1 = u0[0] + u1[0], e2 = g0[1] + g1[1], e3 = u0[1] + u1[1];
            const float e4 = g0[2] + g1[2], e5 = u0[2] + u1[2], e6 = g0[3] + g1[3], e7 = u0[3] + u1[3];
            if (t == 0) st_async4(dst0, e0, e1, e2, e3, dbar0);
            if (t == 0) st_async4(dst1, e4, e5, e6, e7, dbar1);
        }
    }
    if (w >= 8) return;
    {
        const int mt = w & 3, kh = w >> 2;
        uint32_t ad[8][4];
        const uint32_t dst = pin(mapa(sb + OFF_OIN + ((r * 2 + kh) * 16 + (g & 3) * 4) * 4, 2 * mt + (g >> 2))), dbar = pin(mapa(bars + 8 * BAR_O, 2 * mt + (g >> 2)));
        const uint32_t* src = pinp(ptrs.ghh + r * 256 + kh * 128 + (g & 1) * 16 + t * 4);
        uint4 hv[4];
        WAIT(28 + kh);
#pragma unroll
        for (int ks = 0; ks < 8; ks++) {
            int row = (ks >> 1) * 28 + (ks & 1) * 16 + lrow + 8 * lm2;
            if (ks == 7) row = row < 112 ? row : 0;
            ldsm4t(ad[ks], sb + (4 + kh) * SLOT + row * 128 + (((2 * mt + lm1) ^ (row & 7)) << 4));
        }
        for (int it = 0;; it++) {
#pragma unroll
            for (int i = 0; i < 4; i++) hv[i] = ldg_rlx4(src + i * 32);
            uint32_t mx = max(max(hv[0].x, hv[0].y), max(hv[0].z, hv[0].w));
#pragma unroll
            for (int i = 1; i < 4; i++) mx = max(mx, max(max(hv[i].x, hv[i].y), max(hv[i].z, hv[i].w)));
            if (!__any_sync(~0u, mx == EMPTY)) break;
            if (it > (1 << 20)) __trap();
        }
        float c0[4] = {0.f, 0.f, 0.f, 0.f}, c1[4] = {0.f, 0.f, 0.f, 0.f}, c2[4] = {0.f, 0.f, 0.f, 0.f}, c3[4] = {0.f, 0.f, 0.f, 0.f};
        mma(c0, ad[0], hv[0].x, hv[0].y); mma(c1, ad[1], hv[0].z, hv[0].w); mma(c2, ad[2], hv[1].x, hv[1].y); mma(c3, ad[3], hv[1].z, hv[1].w);
        mma(c0, ad[4], hv[2].x, hv[2].y); mma(c1, ad[5], hv[2].z, hv[2].w); mma(c2, ad[6], hv[3].x, hv[3].y); mma(c3, ad[7], hv[3].z, hv[3].w);
        {
            const float e0 = (c0[0] + c1[0]) + (c2[0] + c3[0]), e1 = (c0[1] + c1[1]) + (c2[1] + c3[1]);
            const float e2 = (c0[2] + c1[2]) + (c2[2] + c3[2]), e3 = (c0[3] + c1[3]) + (c2[3] + c3[3]);
            if (t == 0) st_async4(dst, e0, e1, e2, e3, dbar);
        }
    }
}

typedef CUresult (*EncodeFn)(CUtensorMap*, CUtensorMapDataType, cuuint32_t, void*, const cuuint64_t*, const cuuint64_t*, const cuuint32_t*,
                             const cuuint32_t*, CUtensorMapInterleave, CUtensorMapSwizzle, CUtensorMapL2promotion, CUtensorMapFloatOOBfill);

bool make_map(EncodeFn enc, CUtensorMap* m, const void* base, int rank, cuuint64_t d0, cuuint64_t d1, cuuint64_t d2, cuuint64_t s1, cuuint64_t s2,
              cuuint32_t b0, cuuint32_t b1, cuuint32_t b2, CUtensorMapSwizzle sw) {
    cuuint64_t gd[3] = {d0, d1, d2}, gs[2] = {s1, s2};
    cuuint32_t bd[3] = {b0, b1, b2}, es[3] = {1, 1, 1};
    return enc(m, CU_TENSOR_MAP_DATA_TYPE_BFLOAT16, rank, const_cast<void*>(base), gd, gs, bd, es, CU_TENSOR_MAP_INTERLEAVE_NONE, sw,
               CU_TENSOR_MAP_L2_PROMOTION_NONE, CU_TENSOR_MAP_FLOAT_OOB_FILL_NONE) == CUDA_SUCCESS;
}

}

extern "C" void kernel_launch(void* const* d_in, const int* in_sizes, int n_in, void* d_out, int out_size) {
    static EncodeFn enc = nullptr;
    static void *gy = nullptr, *ghh = nullptr, *gready = nullptr;
    static unsigned int pace = 324;
    if (!enc) {
        void* f = nullptr;
        cudaDriverEntryPointQueryResult qr;
        cudaGetDriverEntryPoint("cuTensorMapEncodeTiled", &f, cudaEnableDefault, &qr);
        enc = (EncodeFn)f;
        cudaGetSymbolAddress(&gy, g_y);
        cudaGetSymbolAddress(&ghh, g_hh);
        cudaGetSymbolAddress(&gready, g_ready);
        int dev = 0, khz = 0, bits = 0;
        cudaGetDevice(&dev);
        cudaDeviceGetAttribute(&khz, cudaDevAttrMemoryClockRate, dev);
        cudaDeviceGetAttribute(&bits, cudaDevAttrGlobalMemoryBusWidth, dev);
        if (khz > 0 && bits > 0) pace = (unsigned int)(1048576.0 * 1.0358e9 / ((double)khz * 1e3 * 2.0 * bits / 8.0) + 0.5);
        cudaFuncSetAttribute(fused_decode_kernel, cudaFuncAttributeMaxDynamicSharedMemorySize, SMEM_BYTES);
    }
    CUtensorMap mq, mk, mv, mo, mg, mu, md;
    const CUtensorMapSwizzle S128 = CU_TENSOR_MAP_SWIZZLE_128B, S64 = CU_TENSOR_MAP_SWIZZLE_64B;
    bool ok = true;
    ok &= make_map(enc, &mq, d_in[3], 2, 4096, 512, 1, 8192, 0, 64, 128, 1, S128);
    ok &= make_map(enc, &mk, d_in[1], 3, 64, 131072, 2, 256, 128, 64, 64, 2, S128);
    ok &= make_map(enc, &mv, d_in[2], 3, 64, 131072, 2, 256, 128, 64, 64, 2, S128);
    ok &= make_map(enc, &mo, d_in[4], 2, 512, 4096, 1, 1024, 0, 64, 128, 1, S128);
    ok &= make_map(enc, &mg, d_in[6], 3, 32, 512, 56, 3584, 64, 32, 16, 7, S64);
    ok &= make_map(enc, &mu, d_in[7], 3, 32, 512, 56, 3584, 64, 32, 16, 7, S64);
    ok &= make_map(enc, &md, d_in[8], 2, 512, 1792, 1, 1024, 0, 64, 112, 1, S128);
    if (!ok) return;
    const Ptrs ptrs = {(const bf16*)d_in[0], (bf16*)d_out, (uint32_t*)gy, (uint32_t*)ghh, (uint32_t*)gready, (const unsigned char*)d_in[3], (const unsigned char*)d_in[1],
                       (const unsigned char*)d_in[2], (const unsigned char*)d_in[4], (const unsigned char*)d_in[6], (const unsigned char*)d_in[7], (const unsigned char*)d_in[8], pace};
    fused_decode_kernel<<<NCTA, NTHREADS, SMEM_BYTES, cudaStreamPerThread>>>(ptrs, mq, mk, mv, mo, mg, mu, md);
}
```
